```python
import torch

def _softmax(x, axis=-1):
    return torch.softmax(x, dim=axis)
def _gelu(x):
    return torch.nn.functional.gelu(x, approximate="tanh")
def _silu(x):
    return torch.nn.functional.silu(x)
def _sigmoid(x):
    return torch.sigmoid(x)
def _layernorm(x, axis=-1, eps=1e-5):
    m = x.mean(dim=axis, keepdim=True)
    v = x.var(dim=axis, keepdim=True, unbiased=False)
    return (x - m) / torch.sqrt(v + eps)
def _scatter_add(tgt, idx, src, axis=0):
    return tgt.clone().index_add_(axis, idx, src)
def _segment_sum(src, seg, n):
    out = torch.zeros((n,) + src.shape[1:], dtype=src.dtype)
    return out.index_add_(0, seg, src)
def _pad(x, pw):
    flat = tuple(v for pair in reversed(pw) for v in pair)
    return torch.nn.functional.pad(x, flat)

kernel_name = 'concat_heads__linear_kernel_hedgehog__softmax_full_mha__prompt'

def setup_inputs():

    _w = (lambda a: (lambda t: t.to(torch.bfloat16) if t.is_floating_point() else t)(torch.as_tensor(a)))
    def _A_setup():
        B, S, D, H = 1, 2048, 1024, 32
        Dh = D // H
        return {
            "x": _w((lambda *s: torch.randn(*s, dtype=torch.bfloat16) * 0.4)(B, S, D)),
            "wqkv": _w((lambda *s: torch.randn(*s, dtype=torch.bfloat16) * 0.4)(D, 3 * D)),
            "w_phi": _w((lambda *s: torch.randn(*s, dtype=torch.bfloat16) * 0.4)(H, Dh, Dh) * (Dh ** -0.5)),
            "wo": _w((lambda *s: torch.randn(*s, dtype=torch.bfloat16) * 0.05)(D, D)),
        }
    _A_in = _A_setup()

    def _B_setup():
        B, S, D = 1, 2048, 1024
        return {
            "x": _w((lambda *s: torch.randn(*s, dtype=torch.bfloat16) * 0.2)(B, S, D)),
            "wqkv": _w((lambda *s: torch.randn(*s, dtype=torch.bfloat16) * 0.2)(D, 3 * D)),
            "wo": _w((lambda *s: torch.randn(*s, dtype=torch.bfloat16) * 0.05)(D, D)),
        }
    _B_in = _B_setup()

    return {
        "A_x": _A_in["x"],
        "A_wqkv": _A_in["wqkv"],
        "A_w_phi": _A_in["w_phi"],
        "A_wo": _A_in["wo"],
        "B_x": _B_in["x"],
        "B_wqkv": _B_in["wqkv"],
        "B_wo": _B_in["wo"],
    }

def reference(A_x, A_wqkv, A_w_phi, A_wo, B_x, B_wqkv, B_wo):
    def _A_ref(x, wqkv, w_phi, wo):
        B, S, D = x.shape
        H = 32; Dh = D // H
        qkv = (lambda x, *d: x.permute(*d))((x @ wqkv).reshape(B, S, 3, H, Dh), 2, 0, 3, 1, 4)
        q, k, v = qkv[0], qkv[1], qkv[2]
        pq = torch.einsum("bhsd,hdf->bhsf", q, w_phi)
        pk = torch.einsum("bhsd,hdf->bhsf", k, w_phi)
        phi_q = torch.concatenate([_softmax(pq, axis=-1), _softmax(-pq, axis=-1)], axis=-1)
        phi_k = torch.concatenate([_softmax(pk, axis=-1), _softmax(-pk, axis=-1)], axis=-1)
        kv = torch.einsum("bhsf,bhsd->bhfd", phi_k, v)
        z  = torch.einsum("bhsf->bhf", phi_k)
        num = torch.einsum("bhqf,bhfd->bhqd", phi_q, kv)
        den = torch.einsum("bhqf,bhf->bhq", phi_q, z)[..., None] + 1e-6
        o = num / den
        return (lambda x, *d: x.permute(*d))(o, 0, 2, 1, 3).reshape(B, S, D) @ wo

    def _B_ref(x, wqkv, wo):
        B, S, D = x.shape
        H = 32; Dh = D // H
        qkv = (lambda x, *d: x.permute(*d))((x @ wqkv).reshape(B, S, 3, H, Dh), 2, 0, 3, 1, 4)
        q, k, v = qkv[0], qkv[1], qkv[2]
        scale = Dh ** -0.5
        scores = torch.einsum("bhqd,bhkd->bhqk", q, k) * scale
        p = _softmax(scores, axis=-1)
        o = torch.einsum("bhqk,bhkd->bhqd", p, v)
        return (lambda x, *d: x.permute(*d))(o, 0, 2, 1, 3).reshape(B, S, D) @ wo

    a = _A_ref(A_x, A_wqkv, A_w_phi, A_wo)
    b = _B_ref(B_x, B_wqkv, B_wo)
    return torch.concatenate([a, b], axis=-1)
```

```cpp
#include <cuda_runtime.h>
#include <cuda_bf16.h>
#include <cuda.h>
#include <stdint.h>

namespace hk {

constexpr int SEQ = 2048, DM = 1024, NH = 32;

__device__ __nv_bfloat16 g_qk[2 * NH * SEQ * 32];
__device__ __nv_bfloat16 g_vt[NH * 32 * SEQ];
__device__ __nv_bfloat16 g_o[2 * SEQ * DM];
__device__ uint4 g_phiq[512 * 8 * 128];
__device__ float g_kv[NH * 64 * 40];
__device__ float g_norm[3 * NH * 8];
__device__ unsigned int g_cntB[16], g_cntA[16], g_cntOA[8], g_cntOB[16];
__device__ unsigned int g_epoch[128];

#define STAMP(q) do { } while (0)
struct Params {
    CUtensorMap xB, wB, xA, wA, qk, vtL, vtS, o, woA, woB;
    const __nv_bfloat16 *pxA, *pwA, *pwoA, *pwoB, *wphi;
    __nv_bfloat16* out;
};

constexpr int R1_A = 256 * 64 * 2, R1_B = 192 * 64 * 2, R1_STAGE = R1_A + R1_B, R1_N = 3;
constexpr int VST_OFF = R1_N * R1_STAGE;
constexpr int G_STAGE = 16384, G_N = 5;
constexpr int KV_OFF = G_N * G_STAGE, KV_STAGE = 18432, KV_N = 4;
constexpr int Q_OFF = KV_OFF + KV_N * KV_STAGE;
constexpr int SCR_OFF = Q_OFF + 32768;
constexpr int QST_OFF = SCR_OFF + 26624;
constexpr int WPHI_OFF = QST_OFF + 8192;
constexpr int BAR_OFF = WPHI_OFF + 4096;
constexpr int R3_A = 128 * 64 * 2, R3_STAGE = R3_A + 256 * 64 * 2, R3_N = 4;
constexpr int SMEM_BYTES = BAR_OFF + 1024 + 1024;
static_assert(R3_N * R3_STAGE <= WPHI_OFF, "ring3");
static_assert(VST_OFF + 32768 <= WPHI_OFF, "staging");
static_assert(SMEM_BYTES <= 232448, "smem");
constexpr int B_FULL1 = 0, B_EMPTY1 = 3, B_KVFULL = 6, B_KVEMPTY = 10, B_QFULL = 14, B_GFULL = 16, B_GEMPTY = 21, B_FULL3 = 26, B_EMPTY3 = 30,
              B_R1FREE = 34, B_P1DONE = 35, B_P2DONE = 36, B_COUNT = 37;
constexpr int NORM_OFF = BAR_OFF + 512;

__device__ __forceinline__ uint32_t smem_u32(const void* p) { return (uint32_t)__cvta_generic_to_shared(p); }
__device__ __forceinline__ void mbar_init(uint32_t bar, uint32_t cnt) { asm volatile("mbarrier.init.shared::cta.b64 [%0], %1;" :: "r"(bar), "r"(cnt) : "memory"); }
__device__ __forceinline__ void mbar_expect_tx(uint32_t bar, uint32_t bytes) { asm volatile("mbarrier.arrive.expect_tx.shared::cta.b64 _, [%0], %1;" :: "r"(bar), "r"(bytes) : "memory"); }
__device__ __forceinline__ void mbar_arrive(uint32_t bar) { asm volatile("mbarrier.arrive.shared::cta.b64 _, [%0];" :: "r"(bar) : "memory"); }
__device__ __forceinline__ void mbar_arrive_if(uint32_t bar, bool pred) {
    asm volatile("{\n.reg .pred p;\nsetp.ne.u32 p, %1, 0;\n@p mbarrier.arrive.shared::cta.b64 _, [%0];\n}\n" :: "r"(bar), "r"((uint32_t)pred) : "memory");
}
__device__ __forceinline__ void mbar_wait(uint32_t bar, uint32_t parity) {
    asm volatile("{\n.reg .pred p;\n.reg .u32 c;\nmov.u32 c, 0;\nLAB_WAIT:\nmbarrier.try_wait.parity.shared::cta.b64 p, [%0], %1;\n@p bra LAB_DONE;\n"
                 "add.u32 c, c, 1;\nsetp.lt.u32 p, c, 4194304;\n@p bra LAB_WAIT;\ntrap;\nLAB_DONE:\n}\n" :: "r"(bar), "r"(parity) : "memory");
}
__device__ __forceinline__ void flag_wait(const unsigned int* cnt, unsigned int target) {
    asm volatile("{\n.reg .pred p;\n.reg .u32 c, v;\nmov.u32 c, 0;\nLAB_WAIT:\nld.acquire.gpu.global.u32 v, [%0];\nsub.u32 v, v, %1;\nsetp.ge.s32 p, v, 0;\n@p bra LAB_DONE;\n"
                 "nanosleep.u32 20;\nadd.u32 c, c, 1;\nsetp.lt.u32 p, c, 4194304;\n@p bra LAB_WAIT;\ntrap;\nLAB_DONE:\n}\n" :: "l"(cnt), "r"(target) : "memory");
}
__device__ __forceinline__ void flag_signal(unsigned int* cnt) {
    asm volatile("fence.acq_rel.gpu;\nred.release.gpu.global.add.u32 [%0], 1;" :: "l"(cnt) : "memory");
}
__device__ __forceinline__ void tma2d(uint32_t dst, const CUtensorMap* m, int c0, int c1, uint32_t bar) {
    asm volatile("cp.async.bulk.tensor.2d.shared::cluster.global.mbarrier::complete_tx::bytes [%0], [%1, {%3, %4}], [%2];"
                 :: "r"(dst), "l"(m), "r"(bar), "r"(c0), "r"(c1) : "memory");
}
__device__ __forceinline__ void tma2d_store(const CUtensorMap* m, uint32_t src, int c0, int c1) {
    asm volatile("cp.async.bulk.tensor.2d.global.shared::cta.bulk_group [%0, {%2, %3}], [%1];" :: "l"(m), "r"(src), "r"(c0), "r"(c1) : "memory");
}
__device__ __forceinline__ void bulk_commit() { asm volatile("cp.async.bulk.commit_group;" ::: "memory"); }
__device__ __forceinline__ void bulk_wait_all() { asm volatile("cp.async.bulk.wait_group 0;" ::: "memory"); }
__device__ __forceinline__ void fence_async_smem() { asm volatile("fence.proxy.async.shared::cta;" ::: "memory"); }
__device__ __forceinline__ void fence_async_all() { asm volatile("fence.proxy.async;" ::: "memory"); }
__device__ __forceinline__ void wg_fence() { asm volatile("wgmma.fence.sync.aligned;" ::: "memory"); }
__device__ __forceinline__ void wg_commit() { asm volatile("wgmma.commit_group.sync.aligned;" ::: "memory"); }
template <int N> __device__ __forceinline__ void wg_wait() { asm volatile("wgmma.wait_group.sync.aligned %0;" :: "n"(N) : "memory"); }
__device__ __forceinline__ void bar_sync(int id, int n) { asm volatile("bar.sync %0, %1;" :: "r"(id), "r"(n) : "memory"); }
template <int N> __device__ __forceinline__ void reg_alloc() { asm volatile("setmaxnreg.inc.sync.aligned.u32 %0;" :: "n"(N)); }
template <int N> __device__ __forceinline__ void reg_dealloc() { asm volatile("setmaxnreg.dec.sync.aligned.u32 %0;" :: "n"(N)); }
__device__ __forceinline__ void stsm4(uint32_t addr, uint32_t r0, uint32_t r1, uint32_t r2, uint32_t r3) {
    asm volatile("stmatrix.sync.aligned.m8n8.x4.shared.b16 [%0], {%1, %2, %3, %4};" :: "r"(addr), "r"(r0), "r"(r1), "r"(r2), "r"(r3) : "memory");
}
__device__ __forceinline__ void stsm4_t(uint32_t addr, uint32_t r0, uint32_t r1, uint32_t r2, uint32_t r3) {
    asm volatile("stmatrix.sync.aligned.m8n8.x4.trans.shared.b16 [%0], {%1, %2, %3, %4};" :: "r"(addr), "r"(r0), "r"(r1), "r"(r2), "r"(r3) : "memory");
}
__host__ __device__ constexpr uint64_t desc_hi(uint32_t lbo, uint32_t sbo, int swz) {
    return ((uint64_t)((lbo & 0x3FFFF) >> 4) << 16) | ((uint64_t)((sbo & 0x3FFFF) >> 4) << 32) | ((uint64_t)swz << 62);
}
__device__ __forceinline__ uint64_t desc_lo(uint32_t addr) { return (uint64_t)((addr & 0x3FFFF) >> 4); }
constexpr uint64_t D_K128 = desc_hi(16, 1024, 1);
constexpr uint64_t D_K64 = desc_hi(16, 512, 2);
__device__ __forceinline__ uint32_t pack_bf16(float lo, float hi) {
    uint32_t r; asm("cvt.rn.bf16x2.f32 %0, %1, %2;" : "=r"(r) : "f"(hi), "f"(lo)); return r;
}
__device__ __forceinline__ float bf_lo(uint32_t r) { return __uint_as_float(r << 16); }
__device__ __forceinline__ float bf_hi(uint32_t r) { return __uint_as_float(r & 0xFFFF0000u); }
__device__ __forceinline__ float bf_round(float x) { return __bfloat162float(__float2bfloat16_rn(x)); }
__device__ __forceinline__ float ex2(float x) { float y; asm("ex2.approx.ftz.f32 %0, %1;" : "=f"(y) : "f"(x)); return y; }
template <int R> __device__ __forceinline__ void fence_regs(float (&d)[R]) {
    #pragma unroll
    for (int i = 0; i < R; i++) asm volatile("" : "+f"(d[i]) :: "memory");
}
template <int R> __device__ __forceinline__ void fence_regs(uint32_t (&d)[R]) {
    #pragma unroll
    for (int i = 0; i < R; i++) asm volatile("" : "+r"(d[i]) :: "memory");
}
__device__ __forceinline__ void quad_transpose(uint32_t (&r)[4], int t) {
    uint32_t s0 = (t & 1) ? r[0] : r[1], s1 = (t & 1) ? r[2] : r[3];
    s0 = __shfl_xor_sync(0xffffffffu, s0, 1); s1 = __shfl_xor_sync(0xffffffffu, s1, 1);
    if (t & 1) { r[0] = s0; r[2] = s1; } else { r[1] = s0; r[3] = s1; }
    s0 = (t & 2) ? r[0] : r[2]; s1 = (t & 2) ? r[1] : r[3];
    s0 = __shfl_xor_sync(0xffffffffu, s0, 2); s1 = __shfl_xor_sync(0xffffffffu, s1, 2);
    if (t & 2) { r[0] = s0; r[1] = s1; } else { r[2] = s0; r[3] = s1; }
}
template <int R> __device__ __forceinline__ void pack32(const float (&a)[R], int b0, int rr, float scale, uint32_t (&r)[4]) {
    #pragma unroll
    for (int b = 0; b < 4; b++) r[b] = pack_bf16(a[4 * (b0 + b) + 2 * rr] * scale, a[4 * (b0 + b) + 2 * rr + 1] * scale);
}
__device__ __forceinline__ float sumsq4(const uint32_t (&r)[4]) {
    float s = 0.f;
    #pragma unroll
    for (int b = 0; b < 4; b++) { float lo = bf_lo(r[b]), hi = bf_hi(r[b]); s = fmaf(lo, lo, s); s = fmaf(hi, hi, s); }
    s += __shfl_xor_sync(0xffffffffu, s, 1); s += __shfl_xor_sync(0xffffffffu, s, 2);
    return s;
}

__device__ __forceinline__ void wg_ss_n192_tb(float (&d)[96], uint64_t da, uint64_t db, int sd) {
    asm volatile("{\n.reg .pred p;\nsetp.ne.b32 p, %98, 0;\n"
        "wgmma.mma_async.sync.aligned.m64n192k16.f32.bf16.bf16 {"
        "%0, %1, %2, %3, %4, %5, %6, %7, %8, %9, %10, %11, %12, %13, %14, %15, "
        "%16, %17, %18, %19, %20, %21, %22, %23, %24, %25, %26, %27, %28, %29, %30, %31, "
        "%32, %33, %34, %35, %36, %37, %38, %39, %40, %41, %42, %43, %44, %45, %46, %47, "
        "%48, %49, %50, %51, %52, %53, %54, %55, %56, %57, %58, %59, %60, %61, %62, %63, "
        "%64, %65, %66, %67, %68, %69, %70, %71, %72, %73, %74, %75, %76, %77, %78, %79, "
        "%80, %81, %82, %83, %84, %85, %86, %87, %88, %89, %90, %91, %92, %93, %94, %95}, %96, %97, p, 1, 1, 0, 1;\n}\n"
        : "+f"(d[0]), "+f"(d[1]), "+f"(d[2]), "+f"(d[3]), "+f"(d[4]), "+f"(d[5]), "+f"(d[6]), "+f"(d[7]),
          "+f"(d[8]), "+f"(d[9]), "+f"(d[10]), "+f"(d[11]), "+f"(d[12]), "+f"(d[13]), "+f"(d[14]), "+f"(d[15]),
          "+f"(d[16]), "+f"(d[17]), "+f"(d[18]), "+f"(d[19]), "+f"(d[20]), "+f"(d[21]), "+f"(d[22]), "+f"(d[23]),
          "+f"(d[24]), "+f"(d[25]), "+f"(d[26]), "+f"(d[27]), "+f"(d[28]), "+f"(d[29]), "+f"(d[30]), "+f"(d[31]),
          "+f"(d[32]), "+f"(d[33]), "+f"(d[34]), "+f"(d[35]), "+f"(d[36]), "+f"(d[37]), "+f"(d[38]), "+f"(d[39]),
          "+f"(d[40]), "+f"(d[41]), "+f"(d[42]), "+f"(d[43]), "+f"(d[44]), "+f"(d[45]), "+f"(d[46]), "+f"(d[47]),
          "+f"(d[48]), "+f"(d[49]), "+f"(d[50]), "+f"(d[51]), "+f"(d[52]), "+f"(d[53]), "+f"(d[54]), "+f"(d[55]),
          "+f"(d[56]), "+f"(d[57]), "+f"(d[58]), "+f"(d[59]), "+f"(d[60]), "+f"(d[61]), "+f"(d[62]), "+f"(d[63]),
          "+f"(d[64]), "+f"(d[65]), "+f"(d[66]), "+f"(d[67]), "+f"(d[68]), "+f"(d[69]), "+f"(d[70]), "+f"(d[71]),
          "+f"(d[72]), "+f"(d[73]), "+f"(d[74]), "+f"(d[75]), "+f"(d[76]), "+f"(d[77]), "+f"(d[78]), "+f"(d[79]),
          "+f"(d[80]), "+f"(d[81]), "+f"(d[82]), "+f"(d[83]), "+f"(d[84]), "+f"(d[85]), "+f"(d[86]), "+f"(d[87]),
          "+f"(d[88]), "+f"(d[89]), "+f"(d[90]), "+f"(d[91]), "+f"(d[92]), "+f"(d[93]), "+f"(d[94]), "+f"(d[95])
        : "l"(da), "l"(db), "r"(sd));
}
__device__ __forceinline__ void wg_ss_n128_tb(float (&d)[64], uint64_t da, uint64_t db, int sd) {
    asm volatile("{\n.reg .pred p;\nsetp.ne.b32 p, %66, 0;\n"
        "wgmma.mma_async.sync.aligned.m64n128k16.f32.bf16.bf16 {"
        "%0, %1, %2, %3, %4, %5, %6, %7, %8, %9, %10, %11, %12, %13, %14, %15, "
        "%16, %17, %18, %19, %20, %21, %22, %23, %24, %25, %26, %27, %28, %29, %30, %31, "
        "%32, %33, %34, %35, %36, %37, %38, %39, %40, %41, %42, %43, %44, %45, %46, %47, "
        "%48, %49, %50, %51, %52, %53, %54, %55, %56, %57, %58, %59, %60, %61, %62, %63}, %64, %65, p, 1, 1, 0, 1;\n}\n"
        : "+f"(d[0]), "+f"(d[1]), "+f"(d[2]), "+f"(d[3]), "+f"(d[4]), "+f"(d[5]), "+f"(d[6]), "+f"(d[7]),
          "+f"(d[8]), "+f"(d[9]), "+f"(d[10]), "+f"(d[11]), "+f"(d[12]), "+f"(d[13]), "+f"(d[14]), "+f"(d[15]),
          "+f"(d[16]), "+f"(d[17]), "+f"(d[18]), "+f"(d[19]), "+f"(d[20]), "+f"(d[21]), "+f"(d[22]), "+f"(d[23]),
          "+f"(d[24]), "+f"(d[25]), "+f"(d[26]), "+f"(d[27]), "+f"(d[28]), "+f"(d[29]), "+f"(d[30]), "+f"(d[31]),
          "+f"(d[32]), "+f"(d[33]), "+f"(d[34]), "+f"(d[35]), "+f"(d[36]), "+f"(d[37]), "+f"(d[38]), "+f"(d[39]),
          "+f"(d[40]), "+f"(d[41]), "+f"(d[42]), "+f"(d[43]), "+f"(d[44]), "+f"(d[45]), "+f"(d[46]), "+f"(d[47]),
          "+f"(d[48]), "+f"(d[49]), "+f"(d[50]), "+f"(d[51]), "+f"(d[52]), "+f"(d[53]), "+f"(d[54]), "+f"(d[55]),
          "+f"(d[56]), "+f"(d[57]), "+f"(d[58]), "+f"(d[59]), "+f"(d[60]), "+f"(d[61]), "+f"(d[62]), "+f"(d[63])
        : "l"(da), "l"(db), "r"(sd));
}
__device__ __forceinline__ void wg_ss_n64(float (&d)[32], uint64_t da, uint64_t db, int sd) {
    asm volatile("{\n.reg .pred p;\nsetp.ne.b32 p, %34, 0;\n"
        "wgmma.mma_async.sync.aligned.m64n64k16.f32.bf16.bf16 {"
        "%0, %1, %2, %3, %4, %5, %6, %7, %8, %9, %10, %11, %12, %13, %14, %15, "
        "%16, %17, %18, %19, %20, %21, %22, %23, %24, %25, %26, %27, %28, %29, %30, %31}, %32, %33, p, 1, 1, 0, 0;\n}\n"
        : "+f"(d[0]), "+f"(d[1]), "+f"(d[2]), "+f"(d[3]), "+f"(d[4]), "+f"(d[5]), "+f"(d[6]), "+f"(d[7]),
          "+f"(d[8]), "+f"(d[9]), "+f"(d[10]), "+f"(d[11]), "+f"(d[12]), "+f"(d[13]), "+f"(d[14]), "+f"(d[15]),
          "+f"(d[16]), "+f"(d[17]), "+f"(d[18]), "+f"(d[19]), "+f"(d[20]), "+f"(d[21]), "+f"(d[22]), "+f"(d[23]),
          "+f"(d[24]), "+f"(d[25]), "+f"(d[26]), "+f"(d[27]), "+f"(d[28]), "+f"(d[29]), "+f"(d[30]), "+f"(d[31])
        : "l"(da), "l"(db), "r"(sd));
}
__device__ __forceinline__ void wg_rs_n40(float (&d)[20], uint32_t a0, uint32_t a1, uint32_t a2, uint32_t a3, uint64_t db, int sd) {
    asm volatile("{\n.reg .pred p;\nsetp.ne.b32 p, %25, 0;\n"
        "wgmma.mma_async.sync.aligned.m64n40k16.f32.bf16.bf16 {"
        "%0, %1, %2, %3, %4, %5, %6, %7, %8, %9, %10, %11, %12, %13, %14, %15, "
        "%16, %17, %18, %19}, {%20, %21, %22, %23}, %24, p, 1, 1, 0;\n}\n"
        : "+f"(d[0]), "+f"(d[1]), "+f"(d[2]), "+f"(d[3]), "+f"(d[4]), "+f"(d[5]), "+f"(d[6]), "+f"(d[7]),
          "+f"(d[8]), "+f"(d[9]), "+f"(d[10]), "+f"(d[11]), "+f"(d[12]), "+f"(d[13]), "+f"(d[14]), "+f"(d[15]),
          "+f"(d[16]), "+f"(d[17]), "+f"(d[18]), "+f"(d[19])
        : "r"(a0), "r"(a1), "r"(a2), "r"(a3), "l"(db), "r"(sd));
}
__device__ __forceinline__ void wg_rs_n32(float (&d)[16], uint32_t a0, uint32_t a1, uint32_t a2, uint32_t a3, uint64_t db, int sd) {
    asm volatile("{\n.reg .pred p;\nsetp.ne.b32 p, %21, 0;\n"
        "wgmma.mma_async.sync.aligned.m64n32k16.f32.bf16.bf16 {"
        "%0, %1, %2, %3, %4, %5, %6, %7, %8, %9, %10, %11, %12, %13, %14, %15}, {%16, %17, %18, %19}, %20, p, 1, 1, 0;\n}\n"
        : "+f"(d[0]), "+f"(d[1]), "+f"(d[2]), "+f"(d[3]), "+f"(d[4]), "+f"(d[5]), "+f"(d[6]), "+f"(d[7]),
          "+f"(d[8]), "+f"(d[9]), "+f"(d[10]), "+f"(d[11]), "+f"(d[12]), "+f"(d[13]), "+f"(d[14]), "+f"(d[15])
        : "r"(a0), "r"(a1), "r"(a2), "r"(a3), "l"(db), "r"(sd));
}
__device__ __forceinline__ void wg_ss_n40_ta(float (&d)[20], uint64_t da, uint64_t db, int sd) {
    asm volatile("{\n.reg .pred p;\nsetp.ne.b32 p, %22, 0;\n"
        "wgmma.mma_async.sync.aligned.m64n40k16.f32.bf16.bf16 {"
        "%0, %1, %2, %3, %4, %5, %6, %7, %8, %9, %10, %11, %12, %13, %14, %15, "
        "%16, %17, %18, %19}, %20, %21, p, 1, 1, 1, 0;\n}\n"
        : "+f"(d[0]), "+f"(d[1]), "+f"(d[2]), "+f"(d[3]), "+f"(d[4]), "+f"(d[5]), "+f"(d[6]), "+f"(d[7]),
          "+f"(d[8]), "+f"(d[9]), "+f"(d[10]), "+f"(d[11]), "+f"(d[12]), "+f"(d[13]), "+f"(d[14]), "+f"(d[15]),
          "+f"(d[16]), "+f"(d[17]), "+f"(d[18]), "+f"(d[19])
        : "l"(da), "l"(db), "r"(sd));
}

__device__ __forceinline__ void p1_epilogue_block(const float (&a)[96], int m, int wg, int w4, int lane, int r, int j, uint32_t sb,
                                                  const Params& P, float (&nmax)[6]) {
    const int t = lane & 3;
    const int row = r * 256 + wg * 128 + m * 64 + w4 * 16 + (lane >> 2);
    const float QS = 0.17677669529663687f * 1.4426950408889634f;
    #pragma unroll
    for (int X = 0; X < 2; X++) {
        #pragma unroll
        for (int hh = 0; hh < 2; hh++) {
            #pragma unroll
            for (int rr = 0; rr < 2; rr++) {
                uint32_t v[4];
                pack32(a, X * 8 + hh * 4, rr, X == 0 ? QS : 1.f, v);
                nmax[X * 2 + hh] = fmaxf(nmax[X * 2 + hh], sumsq4(v));
                quad_transpose(v, t);
                *(uint4*)(g_qk + ((size_t)(X * NH + 2 * j + hh) * SEQ + row + 8 * rr) * 32 + t * 8) = make_uint4(v[0], v[1], v[2], v[3]);
            }
        }
    }
    const uint32_t base = sb + VST_OFF + (wg * 2 + m) * 8192;
    const int mat = lane >> 3, i = lane & 7;
    #pragma unroll
    for (int hh = 0; hh < 2; hh++) {
        uint32_t vl[4], vh[4];
        pack32(a, 16 + hh * 4, 0, 1.f, vl);
        pack32(a, 16 + hh * 4, 1, 1.f, vh);
        nmax[4 + hh] = fmaxf(nmax[4 + hh], fmaxf(sumsq4(vl), sumsq4(vh)));
        #pragma unroll
        for (int bp = 0; bp < 2; bp++) {
            const int rowd = hh * 32 + 8 * (2 * bp + (mat >> 1)) + i, chunk = 2 * w4 + (mat & 1);
            stsm4_t(base + rowd * 128 + ((chunk ^ i) << 4), vl[2 * bp], vh[2 * bp], vl[2 * bp + 1], vh[2 * bp + 1]);
        }
    }
    fence_async_smem();
    bar_sync(1 + wg, 128);
    if (w4 == 0 && lane == 0) { tma2d_store(&P.vtS, base, r * 256 + wg * 128 + m * 64, j * 64); bulk_commit(); }
}

__device__ __forceinline__ void phase1(uint32_t sb, uint8_t* sp, int wg, int w4, int lane, int r, int j, const Params& P, long long t0) {
    const uint32_t bars = sb + BAR_OFF;
    const bool elect = (w4 == 0 && lane == 0);
    float a0[96], a1[96];
    #pragma unroll 1
    for (int ks = 0; ks < 16; ks++) {
        const int s = ks % R1_N;
        mbar_wait(bars + (B_FULL1 + s) * 8, (ks / R1_N) & 1);
        const uint32_t st = sb + s * R1_STAGE;
        const uint64_t da = D_K128 | desc_lo(st + wg * 16384);
        const uint64_t db = desc_hi(8192, 1024, 1) | desc_lo(st + R1_A);
        wg_fence();
        #pragma unroll
        for (int k = 0; k < 4; k++) {
            wg_ss_n192_tb(a0, da + k * 2, db + k * 128, (ks > 0 || k > 0) ? 1 : 0);
            wg_ss_n192_tb(a1, da + 512 + k * 2, db + k * 128, (ks > 0 || k > 0) ? 1 : 0);
        }
        wg_commit();
        wg_wait<0>();
        mbar_arrive_if(bars + (B_EMPTY1 + s) * 8, elect);
    }
    fence_regs(a0); fence_regs(a1);
    mbar_arrive_if(bars + B_R1FREE * 8, elect);
    if (wg == 0) STAMP(0);
    float nmax[6] = {0.f, 0.f, 0.f, 0.f, 0.f, 0.f};
    p1_epilogue_block(a0, 0, wg, w4, lane, r, j, sb, P, nmax);
    p1_epilogue_block(a1, 1, wg, w4, lane, r, j, sb, P, nmax);
    #pragma unroll
    for (int q = 0; q < 6; q++) {
        float v = nmax[q];
        v = fmaxf(v, __shfl_xor_sync(0xffffffffu, v, 4)); v = fmaxf(v, __shfl_xor_sync(0xffffffffu, v, 8)); v = fmaxf(v, __shfl_xor_sync(0xffffffffu, v, 16));
        if (lane == 0) atomicMax((unsigned int*)(sp + NORM_OFF) + q, __float_as_uint(v));
    }
    if (elect) { bulk_wait_all(); fence_async_all(); }
    bar_sync(3, 256);
    const int tid = wg * 128 + w4 * 32 + lane;
    if (tid == 0) {
        #pragma unroll
        for (int q = 0; q < 6; q++) g_norm[((q >> 1) * NH + 2 * j + (q & 1)) * 8 + r] = __uint_as_float(*((volatile unsigned int*)(sp + NORM_OFF) + q));
        flag_signal(&g_cntB[j]);
    }
    for (int i = tid; i < KV_N * 2 * 256; i += 256) {
        const int st = i >> 9, sub = (i >> 8) & 1, w = i & 255;
        *(uint32_t*)(sp + KV_OFF + st * KV_STAGE + 8192 + sub * 5120 + 4096 + w * 4) = (w < 32) ? 0x3F803F80u : 0u;
    }
    fence_async_smem();
    bar_sync(3, 256);
    if (tid == 0) mbar_arrive(bars + B_P1DONE * 8);
    if (wg == 0) STAMP(1);
}

__device__ __forceinline__ void exp_pack(const float (&s)[32], uint32_t (&p)[16]) {
    #pragma unroll
    for (int i = 0; i < 16; i++) p[i] = pack_bf16(ex2(s[2 * i]), ex2(s[2 * i + 1]));
}
__device__ __forceinline__ void qk_issue(float (&s)[32], uint64_t dq, uint64_t dk) {
    wg_ss_n64(s, dq, dk, 0);
    wg_ss_n64(s, dq + 2, dk + 2, 1);
}
__device__ __forceinline__ void pv_issue(float (&o)[20], const uint32_t (&p)[16], uint64_t dv) {
    #pragma unroll
    for (int k = 0; k < 4; k++) wg_rs_n40(o, p[4 * k], p[4 * k + 1], p[4 * k + 2], p[4 * k + 3], dv + 2 * k, 1);
}
__device__ __forceinline__ void online_exp_pack(float (&s)[32], uint32_t (&p)[16], float (&o)[20], float (&mx)[2]) {
    #pragma unroll
    for (int rr = 0; rr < 2; rr++) {
        float m = mx[rr];
        #pragma unroll
        for (int b = 0; b < 8; b++) m = fmaxf(m, fmaxf(s[4 * b + 2 * rr], s[4 * b + 2 * rr + 1]));
        m = fmaxf(m, __shfl_xor_sync(0xffffffffu, m, 1)); m = fmaxf(m, __shfl_xor_sync(0xffffffffu, m, 2));
        const float sc = ex2(mx[rr] - m);
        mx[rr] = m;
        #pragma unroll
        for (int b = 0; b < 5; b++) { o[4 * b + 2 * rr] *= sc; o[4 * b + 2 * rr + 1] *= sc; }
        #pragma unroll
        for (int b = 0; b < 8; b++) p[2 * b + rr] = pack_bf16(ex2(s[4 * b + 2 * rr] - m), ex2(s[4 * b + 2 * rr + 1] - m));
    }
}
__device__ __forceinline__ void attn_store(const float (&o)[20], int row, int h, int lane) {
    const int t = lane & 3;
    #pragma unroll
    for (int rr = 0; rr < 2; rr++) {
        const float l = __shfl_sync(0xffffffffu, o[16 + 2 * rr], lane & ~3);
        uint32_t v[4];
        pack32(o, 0, rr, 1.f / l, v);
        quad_transpose(v, t);
        *(uint4*)(g_o + (size_t)SEQ * DM + (size_t)(row + 8 * rr) * DM + h * 32 + t * 8) = make_uint4(v[0], v[1], v[2], v[3]);
    }
}

__device__ __forceinline__ void attention(uint32_t sb, int wg, int w4, int lane, int r, int j, long long t0) {
    const uint32_t bars = sb + BAR_OFF;
    const bool elect = (w4 == 0 && lane == 0);
    #pragma unroll 1
    for (int task = 0; task < 2; task++) {
        const int h = j + 16 * task;
        mbar_wait(bars + (B_QFULL + task) * 8, 0);
        if (wg == 0 && task == 0) STAMP(2);
        float nk = 0.f, nv = 0.f;
        #pragma unroll
        for (int i = 0; i < 8; i++) { nk = fmaxf(nk, __ldcg(&g_norm[(NH + h) * 8 + i])); nv = fmaxf(nv, __ldcg(&g_norm[(2 * NH + h) * 8 + i])); }
        const float nq = __ldcg(&g_norm[h * 8 + r]);
        const bool safe = (nq * nk <= 3600.f) && (nv <= 1e24f) && (nq <= 1e18f) && (nk <= 1e18f);
        const uint64_t dqa = D_K64 | desc_lo(sb + Q_OFF + task * 16384 + wg * 8192), dqb = dqa + 256;
        float oa[20], ob[20], sa[32], sc[32];
        uint32_t pa[16], pb[16];
        #pragma unroll
        for (int i = 0; i < 20; i++) { oa[i] = 0.f; ob[i] = 0.f; }
        fence_regs(oa); fence_regs(ob);
        const uint64_t dk0 = D_K64 | desc_lo(sb + KV_OFF), dv0 = D_K128 | desc_lo(sb + KV_OFF + 8192);
        if (safe) {
            #pragma unroll 1
            for (int body = 0; body < 4; body++) {
                const uint32_t par = (task * 4 + body) & 1;
                mbar_wait(bars + B_KVFULL * 8, par);
                wg_fence();
                qk_issue(sa, dqa, dk0); wg_commit();
                qk_issue(sc, dqb, dk0); wg_commit();
                #pragma unroll
                for (int q = 0; q < 8; q++) {
                    const int u = q >> 1, half = q & 1, qn = q + 1;
                    const uint64_t dv = dv0 + u * (KV_STAGE >> 4) + half * (5120 >> 4);
                    const uint64_t dkn = dk0 + (qn >> 1) * (KV_STAGE >> 4) + (qn & 1) * (4096 >> 4);
                    wg_wait<1>();
                    fence_regs(sa);
                    exp_pack(sa, pa);
                    if (half == 1 && qn < 8) mbar_wait(bars + (B_KVFULL + u + 1) * 8, par);
                    fence_regs(pa);
                    wg_fence();
                    pv_issue(oa, pa, dv);
                    if (qn < 8) qk_issue(sa, dqa, dkn);
                    wg_commit();
                    wg_wait<1>();
                    fence_regs(sc);
                    if (half == 0 && u > 0) mbar_arrive_if(bars + (B_KVEMPTY + u - 1) * 8, elect);
                    exp_pack(sc, pb);
                    fence_regs(pb);
                    wg_fence();
                    pv_issue(ob, pb, dv);
                    if (qn < 8) qk_issue(sc, dqb, dkn);
                    wg_commit();
                }
                wg_wait<0>();
                fence_regs(oa); fence_regs(ob);
                mbar_arrive_if(bars + (B_KVEMPTY + 3) * 8, elect);
            }
        } else {
            float ma[2] = {-INFINITY, -INFINITY}, mb[2] = {-INFINITY, -INFINITY};
            #pragma unroll 1
            for (int q = 0; q < 32; q++) {
                const int u = (q >> 1) & 3, half = q & 1;
                const uint32_t par = (task * 4 + (q >> 3)) & 1;
                if (half == 0) mbar_wait(bars + (B_KVFULL + u) * 8, par);
                const uint64_t dk = dk0 + u * (KV_STAGE >> 4) + half * (4096 >> 4);
                const uint64_t dv = dv0 + u * (KV_STAGE >> 4) + half * (5120 >> 4);
                wg_fence();
                qk_issue(sa, dqa, dk);
                qk_issue(sc, dqb, dk);
                wg_commit();
                wg_wait<0>();
                fence_regs(sa); fence_regs(sc);
                online_exp_pack(sa, pa, oa, ma);
                online_exp_pack(sc, pb, ob, mb);
                fence_regs(pa); fence_regs(pb); fence_regs(oa); fence_regs(ob);
                wg_fence();
                pv_issue(oa, pa, dv);
                pv_issue(ob, pb, dv);
                wg_commit();
                wg_wait<0>();
                fence_regs(oa); fence_regs(ob);
                if (half == 1) mbar_arrive_if(bars + (B_KVEMPTY + u) * 8, elect);
            }
        }
        const int row = r * 256 + wg * 128 + w4 * 16 + (lane >> 2);
        attn_store(oa, row, h, lane);
        attn_store(ob, row + 64, h, lane);
        bar_sync(1 + wg, 128);
        if (elect) flag_signal(&g_cntOB[task * 8 + r]);
        if (wg == 0) STAMP(3 + task);
    }
}

__device__ __forceinline__ void phase3(uint32_t sb, int wg, int w4, int lane, int c, const Params& P, long long t0) {
    const uint32_t bars = sb + BAR_OFF;
    const bool elect = (w4 == 0 && lane == 0);
    float a0[64], a1[64];
    #pragma unroll 1
    for (int ks = 0; ks < 16; ks++) {
        const int s = ks & 3;
        mbar_wait(bars + (B_FULL3 + s) * 8, (ks >> 2) & 1);
        if (wg == 0 && ks == 0) STAMP(5);
        const uint32_t st = sb + s * R3_STAGE;
        const uint64_t da = D_K128 | desc_lo(st + wg * 8192);
        const uint64_t db = desc_hi(8192, 1024, 1) | desc_lo(st + R3_A);
        wg_fence();
        #pragma unroll
        for (int k = 0; k < 4; k++) {
            wg_ss_n128_tb(a0, da + k * 2, db + k * 128, (ks > 0 || k > 0) ? 1 : 0);
            wg_ss_n128_tb(a1, da + k * 2, db + 1024 + k * 128, (ks > 0 || k > 0) ? 1 : 0);
        }
        wg_commit();
        wg_wait<0>();
        mbar_arrive_if(bars + (B_EMPTY3 + s) * 8, elect);
    }
    fence_regs(a0); fence_regs(a1);
    if (wg == 0) STAMP(6);
    const int br = c >> 6, rb = c & 15, cb = (c >> 4) & 3, t = lane & 3;
    __nv_bfloat16* dst = P.out + (size_t)(rb * 128 + wg * 64 + w4 * 16 + (lane >> 2)) * 2048 + br * 1024 + cb * 256 + t * 8;
    #pragma unroll
    for (int g = 0; g < 4; g++) {
        #pragma unroll
        for (int rr = 0; rr < 2; rr++) {
            uint32_t v[4];
            pack32(a0, g * 4, rr, 1.f, v);
            quad_transpose(v, t);
            *(uint4*)(dst + (size_t)rr * 8 * 2048 + g * 32) = make_uint4(v[0], v[1], v[2], v[3]);
            pack32(a1, g * 4, rr, 1.f, v);
            quad_transpose(v, t);
            *(uint4*)(dst + (size_t)rr * 8 * 2048 + 128 + g * 32) = make_uint4(v[0], v[1], v[2], v[3]);
        }
    }
}

__device__ __forceinline__ void feature_map(const float (&px)[16], uint32_t (&F)[8][2]) {
    const float L2E = 1.4426950408889634f;
    #pragma unroll
    for (int rr = 0; rr < 2; rr++) {
        float x[8];
        #pragma unroll
        for (int b = 0; b < 4; b++) {
            const uint32_t pk = pack_bf16(px[4 * b + 2 * rr], px[4 * b + 2 * rr + 1]);
            x[2 * b] = bf_lo(pk); x[2 * b + 1] = bf_hi(pk);
        }
        float mx = x[0], mn = x[0];
        #pragma unroll
        for (int i = 1; i < 8; i++) { mx = fmaxf(mx, x[i]); mn = fminf(mn, x[i]); }
        mx = fmaxf(mx, __shfl_xor_sync(0xffffffffu, mx, 1)); mn = fminf(mn, __shfl_xor_sync(0xffffffffu, mn, 1));
        mx = fmaxf(mx, __shfl_xor_sync(0xffffffffu, mx, 2)); mn = fminf(mn, __shfl_xor_sync(0xffffffffu, mn, 2));
        float ep[8], en[8], sp = 0.f, sn = 0.f;
        #pragma unroll
        for (int i = 0; i < 8; i++) {
            ep[i] = ex2((x[i] - mx) * L2E); en[i] = ex2((mn - x[i]) * L2E);
            sp += ep[i]; sn += en[i];
        }
        sp += __shfl_xor_sync(0xffffffffu, sp, 1); sn += __shfl_xor_sync(0xffffffffu, sn, 1);
        sp += __shfl_xor_sync(0xffffffffu, sp, 2); sn += __shfl_xor_sync(0xffffffffu, sn, 2);
        const float ip = __fdividef(1.f, sp), in = __fdividef(1.f, sn);
        #pragma unroll
        for (int b = 0; b < 4; b++) {
            F[b][rr] = pack_bf16(ep[2 * b] * ip, ep[2 * b + 1] * ip);
            F[4 + b][rr] = pack_bf16(en[2 * b] * in, en[2 * b + 1] * in);
        }
    }
}

__device__ __forceinline__ void a_epilogue(const float (&a)[96], uint32_t sb, int w4, int lane, int tile, int j) {
    uint32_t fk[8][2];
    const int mat = lane >> 3, i = lane & 7;
    const uint32_t scr = sb + SCR_OFF;
    const uint32_t qst = sb + QST_OFF + (w4 * 32 + lane) * 16;
    {
        #pragma unroll
        for (int hh = 0; hh < 2; hh++) {
            uint32_t vl[4], vh[4];
            pack32(a, 16 + hh * 4, 0, 1.f, vl);
            pack32(a, 16 + hh * 4, 1, 1.f, vh);
            #pragma unroll
            for (int bp = 0; bp < 2; bp++) {
                const int rowd = 8 * (2 * bp + (mat >> 1)) + i, chunk = 2 * w4 + (mat & 1);
                stsm4_t(scr + 16384 + hh * 5120 + rowd * 128 + ((chunk ^ i) << 4), vl[2 * bp], vh[2 * bp], vl[2 * bp + 1], vh[2 * bp + 1]);
            }
        }
        #pragma unroll
        for (int kk = 0; kk < 4; kk++)
            asm volatile("st.shared.v4.b32 [%0], {%1, %2, %3, %4};" :: "r"(qst + kk * 2048),
                         "r"(pack_bf16(a[8 * kk], a[8 * kk + 1])), "r"(pack_bf16(a[8 * kk + 2], a[8 * kk + 3])),
                         "r"(pack_bf16(a[8 * kk + 4], a[8 * kk + 5])), "r"(pack_bf16(a[8 * kk + 6], a[8 * kk + 7])) : "memory");
        #pragma unroll
        for (int b = 0; b < 8; b++) {
            fk[b][0] = pack_bf16(a[4 * (8 + b)], a[4 * (8 + b) + 1]); fk[b][1] = pack_bf16(a[4 * (8 + b) + 2], a[4 * (8 + b) + 3]);
        }
    }
    #pragma unroll
    for (int hh = 0; hh < 2; hh++) {
        const uint64_t dw = D_K64 | desc_lo(sb + WPHI_OFF + hh * 2048);
        float px[16];
        fence_regs(fk[4 * hh]); fence_regs(fk[4 * hh + 1]); fence_regs(fk[4 * hh + 2]); fence_regs(fk[4 * hh + 3]);
        wg_fence();
        wg_rs_n32(px, fk[4 * hh][0], fk[4 * hh][1], fk[4 * hh + 1][0], fk[4 * hh + 1][1], dw, 0);
        wg_rs_n32(px, fk[4 * hh + 2][0], fk[4 * hh + 2][1], fk[4 * hh + 3][0], fk[4 * hh + 3][1], dw + 2, 1);
        wg_commit();
        wg_wait<0>();
        fence_regs(px);
        uint32_t F[8][2];
        feature_map(px, F);
        #pragma unroll
        for (int bp = 0; bp < 4; bp++) {
            const int srow = w4 * 16 + (mat & 1) * 8 + i, chunk = 2 * bp + (mat >> 1);
            stsm4(scr + hh * 8192 + srow * 128 + ((chunk ^ i) << 4), F[2 * bp][0], F[2 * bp][1], F[2 * bp + 1][0], F[2 * bp + 1][1]);
        }
    }
    fence_async_smem();
    bar_sync(4, 128);
    float kv0[20], kv1[20];
    {
        const uint64_t dA0 = desc_hi(8192, 1024, 1) | desc_lo(scr), dA1 = dA0 + 512;
        const uint64_t dB0 = D_K128 | desc_lo(scr + 16384), dB1 = dB0 + 320;
        wg_fence();
        #pragma unroll
        for (int k = 0; k < 4; k++) wg_ss_n40_ta(kv0, dA0 + k * 128, dB0 + k * 2, k > 0 ? 1 : 0);
        #pragma unroll
        for (int k = 0; k < 4; k++) wg_ss_n40_ta(kv1, dA1 + k * 128, dB1 + k * 2, k > 0 ? 1 : 0);
        wg_commit();
        wg_wait<0>();
        fence_regs(kv0); fence_regs(kv1);
    }
    #pragma unroll
    for (int hh = 0; hh < 2; hh++) {
        float* dst = g_kv + (size_t)((2 * j + hh) * 64 + w4 * 16 + (lane >> 2)) * 40 + (lane & 3) * 2;
        #pragma unroll
        for (int b = 0; b < 5; b++) {
            if (b < 4 || (lane & 3) == 0) {
                #pragma unroll
                for (int rr = 0; rr < 2; rr++) {
                    const float v0 = hh == 0 ? kv0[4 * b + 2 * rr] : kv1[4 * b + 2 * rr], v1 = hh == 0 ? kv0[4 * b + 2 * rr + 1] : kv1[4 * b + 2 * rr + 1];
                    asm volatile("red.global.add.v2.f32 [%0], {%1, %2};" :: "l"(dst + rr * 8 * 40 + b * 8), "f"(v0), "f"(v1) : "memory");
                }
            }
        }
    }
    const int tid = w4 * 32 + lane;
    #pragma unroll
    for (int hh = 0; hh < 2; hh++) {
        const uint64_t dw = D_K64 | desc_lo(sb + WPHI_OFF + hh * 2048);
        float px[16];
        uint32_t fq[8];
        asm volatile("ld.shared.v4.b32 {%0, %1, %2, %3}, [%4];" : "=r"(fq[0]), "=r"(fq[1]), "=r"(fq[2]), "=r"(fq[3]) : "r"(qst + (2 * hh) * 2048));
        asm volatile("ld.shared.v4.b32 {%0, %1, %2, %3}, [%4];" : "=r"(fq[4]), "=r"(fq[5]), "=r"(fq[6]), "=r"(fq[7]) : "r"(qst + (2 * hh + 1) * 2048));
        fence_regs(fq);
        wg_fence();
        wg_rs_n32(px, fq[0], fq[1], fq[2], fq[3], dw, 0);
        wg_rs_n32(px, fq[4], fq[5], fq[6], fq[7], dw + 2, 1);
        wg_commit();
        wg_wait<0>();
        fence_regs(px);
        uint32_t F[8][2];
        feature_map(px, F);
        #pragma unroll
        for (int kk = 0; kk < 4; kk++)
            g_phiq[(size_t)(tile * 8 + hh * 4 + kk) * 128 + tid] = make_uint4(F[2 * kk][0], F[2 * kk][1], F[2 * kk + 1][0], F[2 * kk + 1][1]);
    }
}

__device__ __forceinline__ void a_branch(uint32_t sb, uint8_t* sp, int w4, int lane, int r, int j, unsigned int epoch, const Params& P, long long t0) {
    const uint32_t bars = sb + BAR_OFF;
    const int tid = w4 * 32 + lane;
    const bool elect = (tid == 0);
    mbar_wait(bars + B_P1DONE * 8, 0);
    for (int i = tid; i < 2 * 256; i += 128) {
        const int hh = i >> 8, w = i & 255;
        *(uint32_t*)(sp + SCR_OFF + 16384 + hh * 5120 + 4096 + w * 4) = (w < 32) ? 0x3F803F80u : 0u;
    }
    int it = 0;
    #pragma unroll 1
    for (int i = 0; i < 4; i++) {
        float a[96];
        #pragma unroll
        for (int q = 0; q < 96; q++) a[q] = 0.f;
        fence_regs(a);
        #pragma unroll 1
        for (int ks = 0; ks < 32; ks++, it++) {
            const int s = it % G_N;
            mbar_wait(bars + (B_GFULL + s) * 8, (it / G_N) & 1);
            const uint32_t st = sb + s * G_STAGE;
            const uint64_t da = D_K64 | desc_lo(st);
            const uint64_t db = desc_hi(4096, 1024, 1) | desc_lo(st + 4096);
            wg_fence();
            wg_ss_n192_tb(a, da, db, 1);
            wg_ss_n192_tb(a, da + 2, db + 128, 1);
            wg_commit();
            wg_wait<0>();
            mbar_arrive_if(bars + (B_GEMPTY + s) * 8, elect);
        }
        fence_regs(a);
        if (i == 0) STAMP(8);
        if (i == 0) { if (elect) flag_wait(&g_cntB[j], 8 * (epoch + 1)); }
        bar_sync(4, 128);
        a_epilogue(a, sb, w4, lane, (r * 4 + i) * 16 + j, j);
        if (i == 0) STAMP(9);
        if (i == 3) STAMP(10);
    }
    bar_sync(4, 128);
    if (elect) { flag_signal(&g_cntA[j]); flag_wait(&g_cntA[j], 8 * (epoch + 1)); }
    bar_sync(4, 128);
    for (int i = tid; i < 2 * 40 * 32; i += 128) {
        const int hh = i / 1280, rem = i - hh * 1280, n = rem >> 5, f = (rem & 31) * 2;
        const float* src = g_kv + (size_t)((2 * j + hh) * 64 + f) * 40 + n;
        const float v0 = n <= 32 ? __ldcg(src) : 0.f, v1 = n <= 32 ? __ldcg(src + 40) : 0.f;
        *(uint32_t*)(sp + SCR_OFF + hh * 5120 + n * 128 + (((f >> 3) ^ (n & 7)) << 4) + (f & 7) * 2) = pack_bf16(v0, v1);
    }
    fence_async_smem();
    bar_sync(4, 128);
    #pragma unroll 1
    for (int i = 0; i < 4; i++) {
        const int tile = (r * 4 + i) * 16 + j;
        const int row = r * 256 + i * 64 + w4 * 16 + (lane >> 2), t = lane & 3;
        #pragma unroll
        for (int hh = 0; hh < 2; hh++) {
            uint32_t f[16];
            #pragma unroll
            for (int kk = 0; kk < 4; kk++) {
                const uint4 v = __ldcg(&g_phiq[(size_t)(tile * 8 + hh * 4 + kk) * 128 + tid]);
                f[4 * kk] = v.x; f[4 * kk + 1] = v.y; f[4 * kk + 2] = v.z; f[4 * kk + 3] = v.w;
            }
            float o[20];
            const uint64_t dB = D_K128 | desc_lo(sb + SCR_OFF + hh * 5120);
            fence_regs(f);
            wg_fence();
            #pragma unroll
            for (int kk = 0; kk < 4; kk++) wg_rs_n40(o, f[4 * kk], f[4 * kk + 1], f[4 * kk + 2], f[4 * kk + 3], dB + 2 * kk, kk > 0 ? 1 : 0);
            wg_commit();
            wg_wait<0>();
            fence_regs(o);
            #pragma unroll
            for (int rr = 0; rr < 2; rr++) {
                float den = __shfl_sync(0xffffffffu, o[16 + 2 * rr], lane & ~3);
                den = bf_round(bf_round(den) + 1e-6f);
                uint32_t v[4];
                #pragma unroll
                for (int b = 0; b < 4; b++)
                    v[b] = pack_bf16(bf_round(o[4 * b + 2 * rr]) / den, bf_round(o[4 * b + 2 * rr + 1]) / den);
                quad_transpose(v, t);
                *(uint4*)(g_o + (size_t)(row + 8 * rr) * DM + (2 * j + hh) * 32 + t * 8) = make_uint4(v[0], v[1], v[2], v[3]);
            }
        }
    }
    bar_sync(4, 128);
    if (elect) { flag_signal(&g_cntOA[r]); mbar_arrive(bars + B_P2DONE * 8); }
    STAMP(11);
}

__global__ void __launch_bounds__(512, 1) fused_kernel(const __grid_constant__ Params P) {
    extern __shared__ uint8_t smem_raw[];
    const uint32_t sb = (smem_u32(smem_raw) + 1023) & ~1023u;
    uint8_t* sp = smem_raw + (sb - smem_u32(smem_raw));
    const uint32_t bars = sb + BAR_OFF;
    const int warp = threadIdx.x >> 5, lane = threadIdx.x & 31, wg = warp >> 2, w4 = warp & 3;
    const int c = blockIdx.x, r = c & 7, j = c >> 3;
    if (threadIdx.x == 0) {
        for (int s = 0; s < R1_N; s++) { mbar_init(bars + (B_FULL1 + s) * 8, 1); mbar_init(bars + (B_EMPTY1 + s) * 8, 2); }
        for (int s = 0; s < KV_N; s++) { mbar_init(bars + (B_KVFULL + s) * 8, 1); mbar_init(bars + (B_KVEMPTY + s) * 8, 2); }
        for (int s = 0; s < 2; s++) mbar_init(bars + (B_QFULL + s) * 8, 1);
        for (int s = 0; s < G_N; s++) { mbar_init(bars + (B_GFULL + s) * 8, 1); mbar_init(bars + (B_GEMPTY + s) * 8, 1); }
        for (int s = 0; s < R3_N; s++) { mbar_init(bars + (B_FULL3 + s) * 8, 1); mbar_init(bars + (B_EMPTY3 + s) * 8, 2); }
        mbar_init(bars + B_R1FREE * 8, 2); mbar_init(bars + B_P1DONE * 8, 1); mbar_init(bars + B_P2DONE * 8, 3);
        for (int q = 0; q < 6; q++) *((unsigned int*)(sp + NORM_OFF) + q) = 0u;
        *((unsigned int*)(sp + NORM_OFF) + 6) = g_epoch[c];
        *((unsigned int*)(sp + NORM_OFF) + 7) = 0u;
        asm volatile("fence.mbarrier_init.release.cluster;" ::: "memory");
    }
    __syncthreads();
    const unsigned int epoch = *((volatile unsigned int*)(sp + NORM_OFF) + 6);
    const long long t0 = 0;

    if (wg == 3) {
        reg_dealloc<24>();
        if (warp == 12 && lane == 0) {
            for (int ks = 0; ks < 16; ks++) {
                const int s = ks % R1_N;
                if (ks >= R1_N) mbar_wait(bars + (B_EMPTY1 + s) * 8, ((ks / R1_N) - 1) & 1);
                const uint32_t st = sb + s * R1_STAGE, fb = bars + (B_FULL1 + s) * 8;
                mbar_expect_tx(fb, R1_STAGE);
                tma2d(st, &P.xB, ks * 64, r * 256, fb);
                for (int q = 0; q < 3; q++) tma2d(st + R1_A + q * 8192, &P.wB, q * 1024 + j * 64, ks * 64, fb);
            }
            mbar_wait(bars + B_P1DONE * 8, 0);
            for (int task = 0; task < 2; task++) {
                const int h = j + 16 * task;
                flag_wait(&g_cntB[h >> 1], 8 * (epoch + 1));
                fence_async_all();
                const uint32_t qb = bars + (B_QFULL + task) * 8;
                mbar_expect_tx(qb, 16384);
                for (int u = 0; u < 2; u++) tma2d(sb + Q_OFF + task * 16384 + u * 8192, &P.qk, 0, h * SEQ + r * 256 + u * 128, qb);
                for (int t = 0; t < 16; t++) {
                    const int g = task * 16 + t, s = g & 3;
                    if (g >= KV_N) mbar_wait(bars + (B_KVEMPTY + s) * 8, ((g >> 2) - 1) & 1);
                    const uint32_t st = sb + KV_OFF + s * KV_STAGE, fb = bars + (B_KVFULL + s) * 8;
                    mbar_expect_tx(fb, 16384);
                    tma2d(st, &P.qk, 0, (NH + h) * SEQ + t * 128, fb);
                    tma2d(st + 8192, &P.vtL, t * 128, h * 32, fb);
                    tma2d(st + 8192 + 5120, &P.vtL, t * 128 + 64, h * 32, fb);
                }
            }
            const int br = c >> 6, rb = c & 15, cb = (c >> 4) & 3;
            mbar_wait(bars + B_P2DONE * 8, 0);
            const CUtensorMap* mw = br == 0 ? &P.woA : &P.woB;
            for (int ks = 0; ks < 16; ks++) {
                const int s = ks & 3;
                if (ks == 0) { if (br == 0) flag_wait(&g_cntOA[rb >> 1], 16 * (epoch + 1)); else flag_wait(&g_cntOB[rb >> 1], 32 * (epoch + 1)); fence_async_all(); }
                if (ks == 8 && br == 1) { flag_wait(&g_cntOB[8 + (rb >> 1)], 32 * (epoch + 1)); fence_async_all(); }
                if (ks >= R3_N) mbar_wait(bars + (B_EMPTY3 + s) * 8, ((ks >> 2) - 1) & 1);
                const uint32_t st = sb + s * R3_STAGE, fb = bars + (B_FULL3 + s) * 8;
                mbar_expect_tx(fb, R3_STAGE);
                tma2d(st, &P.o, ks * 64, br * SEQ + rb * 128, fb);
                for (int q = 0; q < 4; q++) tma2d(st + R3_A + q * 8192, mw, cb * 256 + q * 64, ks * 64, fb);
            }
        } else if (warp == 13 && lane == 0) {
            mbar_wait(bars + B_R1FREE * 8, 0);
            for (int it = 0; it < 128; it++) {
                const int s = it % G_N, i = it >> 5, ks = it & 31;
                if (it >= G_N) mbar_wait(bars + (B_GEMPTY + s) * 8, ((it / G_N) - 1) & 1);
                const uint32_t st = sb + s * G_STAGE, fb = bars + (B_GFULL + s) * 8;
                mbar_expect_tx(fb, G_STAGE);
                tma2d(st, &P.xA, ks * 32, r * 256 + i * 64, fb);
                for (int q = 0; q < 3; q++) tma2d(st + 4096 + q * 4096, &P.wA, q * 1024 + j * 64, ks * 32, fb);
            }
        } else if (warp == 14) {
            if (lane < 4) {
                const char* src; uint32_t bytes;
                if (lane == 0) { src = (const char*)P.pxA; bytes = SEQ * DM * 2 / 128; }
                else if (lane == 1) { src = (const char*)P.pwA; bytes = DM * 3 * DM * 2 / 128; }
                else if (lane == 2) { src = (const char*)P.pwoA; bytes = DM * DM * 2 / 128; }
                else { src = (const char*)P.pwoB; bytes = DM * DM * 2 / 128; }
                src += (size_t)c * bytes;
                mbar_wait(bars + B_FULL1 * 8, 0);
                for (uint32_t o = 0; o < bytes; o += 4096)
                    asm volatile("cp.async.bulk.prefetch.L2.global [%0], %1;" :: "l"(src + o), "r"(4096u) : "memory");
            }
        }
    } else if (wg == 2) {
        reg_dealloc<24>();
        for (int i = threadIdx.x & 127; i < 2048; i += 128) {
            const int hh = i >> 10, d = (i >> 5) & 31, f = i & 31;
            *(__nv_bfloat16*)(sp + WPHI_OFF + hh * 2048 + f * 64 + (((d >> 3) ^ ((f >> 1) & 3)) << 4) + (d & 7) * 2) = P.wphi[(size_t)(2 * j + hh) * 1024 + d * 32 + f];
        }
        fence_async_smem();
        reg_alloc<152>();
        a_branch(sb, sp, w4, lane, r, j, epoch, P, t0);
    } else {
        reg_alloc<232>();
        if (r == 0) {
            float4* z = (float4*)(g_kv + (size_t)2 * j * 64 * 40);
            for (int i = threadIdx.x; i < 2 * 64 * 40 / 4; i += 256) z[i] = make_float4(0.f, 0.f, 0.f, 0.f);
        }
        phase1(sb, sp, wg, w4, lane, r, j, P, t0);
        reg_dealloc<168>();
        attention(sb, wg, w4, lane, r, j, t0);
        mbar_arrive_if(bars + B_P2DONE * 8, w4 == 0 && lane == 0);
        phase3(sb, wg, w4, lane, c, P, t0);
        if (threadIdx.x == 0) g_epoch[c] = epoch + 1;
    }
}

typedef CUresult (*EncodeFn)(CUtensorMap*, CUtensorMapDataType, cuuint32_t, void*, const cuuint64_t*, const cuuint64_t*, const cuuint32_t*,
                             const cuuint32_t*, CUtensorMapInterleave, CUtensorMapSwizzle, CUtensorMapL2promotion, CUtensorMapFloatOOBfill);
static void make_map(EncodeFn enc, CUtensorMap* m, const void* ptr, uint64_t inner, uint64_t outer, uint32_t box_inner, uint32_t box_outer, CUtensorMapSwizzle swz) {
    cuuint64_t gd[2] = {inner, outer}; cuuint64_t gs[1] = {inner * 2}; cuuint32_t bd[2] = {box_inner, box_outer}; cuuint32_t es[2] = {1, 1};
    enc(m, CU_TENSOR_MAP_DATA_TYPE_BFLOAT16, 2, const_cast<void*>(ptr), gd, gs, bd, es, CU_TENSOR_MAP_INTERLEAVE_NONE, swz,
        CU_TENSOR_MAP_L2_PROMOTION_L2_128B, CU_TENSOR_MAP_FLOAT_OOB_FILL_NONE);
}

}

extern "C" void kernel_launch(void* const* d_in, const int* in_sizes, int n_in, void* d_out, int out_size) {
    using namespace hk;
    (void)in_sizes; (void)n_in; (void)out_size;
    const __nv_bfloat16* A_x = (const __nv_bfloat16*)d_in[0];
    const __nv_bfloat16* A_wqkv = (const __nv_bfloat16*)d_in[1];
    const __nv_bfloat16* A_wphi = (const __nv_bfloat16*)d_in[2];
    const __nv_bfloat16* A_wo = (const __nv_bfloat16*)d_in[3];
    const __nv_bfloat16* B_x = (const __nv_bfloat16*)d_in[4];
    const __nv_bfloat16* B_wqkv = (const __nv_bfloat16*)d_in[5];
    const __nv_bfloat16* B_wo = (const __nv_bfloat16*)d_in[6];
    static EncodeFn enc = nullptr;
    static void *p_qk = nullptr, *p_vt = nullptr, *p_o = nullptr;
    if (!enc) {
        void* fn = nullptr; cudaDriverEntryPointQueryResult qr;
        cudaGetDriverEntryPoint("cuTensorMapEncodeTiled", &fn, cudaEnableDefault, &qr);
        enc = (EncodeFn)fn;
        cudaGetSymbolAddress(&p_qk, g_qk); cudaGetSymbolAddress(&p_vt, g_vt); cudaGetSymbolAddress(&p_o, g_o);
        cudaFuncSetAttribute(fused_kernel, cudaFuncAttributeMaxDynamicSharedMemorySize, SMEM_BYTES);
    }
    Params P;
    const CUtensorMapSwizzle S128 = CU_TENSOR_MAP_SWIZZLE_128B, S64 = CU_TENSOR_MAP_SWIZZLE_64B;
    make_map(enc, &P.xB, B_x, DM, SEQ, 64, 256, S128);
    make_map(enc, &P.wB, B_wqkv, 3 * DM, DM, 64, 64, S128);
    make_map(enc, &P.xA, A_x, DM, SEQ, 32, 64, S64);
    make_map(enc, &P.wA, A_wqkv, 3 * DM, DM, 64, 32, S128);
    make_map(enc, &P.qk, p_qk, 32, 2 * NH * SEQ, 32, 128, S64);
    make_map(enc, &P.vtL, p_vt, SEQ, NH * 32, 64, 32, S128);
    make_map(enc, &P.vtS, p_vt, SEQ, NH * 32, 64, 64, S128);
    make_map(enc, &P.o, p_o, DM, 2 * SEQ, 64, 128, S128);
    make_map(enc, &P.woA, A_wo, DM, DM, 64, 64, S128);
    make_map(enc, &P.woB, B_wo, DM, DM, 64, 64, S128);
    P.pxA = A_x; P.pwA = A_wqkv; P.pwoA = A_wo; P.pwoB = B_wo; P.wphi = A_wphi;
    P.out = (__nv_bfloat16*)d_out;
    fused_kernel<<<128, 512, SMEM_BYTES, cudaStreamPerThread>>>(P);
}
```

```cpp
#include <cuda_runtime.h>
#include <cuda_bf16.h>
#include <cuda.h>
#include <stdint.h>

namespace hk {

constexpr int SEQ = 2048, DM = 1024, NH = 32;

__device__ uint4 g_kimg[NH * 16 * 512];
__device__ uint4 g_vimg[NH * 32 * 256];
__device__ __nv_bfloat16 g_o[2 * SEQ * DM];
__device__ uint4 g_qfrag[512 * 4 * 128];
__device__ float g_kv[NH * 64 * 40];
__device__ float g_norm[2 * NH * 8];
__device__ unsigned int g_cntB[16], g_cntA[16], g_cntOA[8], g_cntOB[16];
__device__ unsigned int g_epoch[128];

#define STAMP(q) do { } while (0)
#define ASTAMP(q) do { } while (0)
#define GSTAMP(q) do { } while (0)
#define GT1(q) do { } while (0)
struct Params {
    CUtensorMap xB, wB, xA, wA, o, oS, woA, woB, out;
    const __nv_bfloat16 *pxB, *pwB, *pxA, *pwA, *pwoA, *pwoB, *wphi;
};

constexpr int R1_A = 256 * 64 * 2, R1_B = 192 * 64 * 2, R1_STAGE = R1_A + R1_B, R1_N = 3;
constexpr int GW_STAGE = 12288, G_N = 4, GX_OFF = G_N * GW_STAGE, GX_STAGE = 8192;
constexpr int KV_OFF = GX_OFF + 4 * GX_STAGE, KV_STAGE = 18432, KV_N = 4;
constexpr int Q_OFF = KV_OFF + KV_N * KV_STAGE;
constexpr int SCR_OFF = Q_OFF + 32768;
constexpr int WPHI_OFF = SCR_OFF + 26624;
constexpr int BAR_OFF = WPHI_OFF + 4096;
constexpr int R3_A = 128 * 64 * 2, R3_STAGE = R3_A + 256 * 64 * 2, R3_N = 4;
constexpr int SMEM_BYTES = BAR_OFF + 1024 + 1024;
static_assert(R3_N * R3_STAGE <= WPHI_OFF, "ring3");
static_assert(SMEM_BYTES <= 232448, "smem");
constexpr int B_FULL1 = 0, B_EMPTY1 = 3, B_KVFULL = 6, B_KVEMPTY = 10, B_GFULL = 16, B_GEMPTY = 21, B_FULL3 = 26, B_EMPTY3 = 30,
              B_R1FREE = 34, B_P1DONE = 35, B_P2DONE = 36, B_NORMOK = 37, B_ODONE = 38, B_KVDONE = 40, B_ADONE = 41, B_KVSTAGED = 42;
constexpr int NORM_OFF = BAR_OFF + 512;

__device__ __forceinline__ uint32_t smem_u32(const void* p) { return (uint32_t)__cvta_generic_to_shared(p); }
__device__ __forceinline__ void mbar_init(uint32_t bar, uint32_t cnt) { asm volatile("mbarrier.init.shared::cta.b64 [%0], %1;" :: "r"(bar), "r"(cnt) : "memory"); }
__device__ __forceinline__ void mbar_expect_tx(uint32_t bar, uint32_t bytes) { asm volatile("mbarrier.arrive.expect_tx.shared::cta.b64 _, [%0], %1;" :: "r"(bar), "r"(bytes) : "memory"); }
__device__ __forceinline__ void mbar_arrive(uint32_t bar) { asm volatile("mbarrier.arrive.shared::cta.b64 _, [%0];" :: "r"(bar) : "memory"); }
__device__ __forceinline__ void mbar_arrive_if(uint32_t bar, bool pred) {
    asm volatile("{\n.reg .pred p;\nsetp.ne.u32 p, %1, 0;\n@p mbarrier.arrive.shared::cta.b64 _, [%0];\n}\n" :: "r"(bar), "r"((uint32_t)pred) : "memory");
}
__device__ __forceinline__ void mbar_wait(uint32_t bar, uint32_t parity) {
    asm volatile("{\n.reg .pred p;\n.reg .u32 c;\nmov.u32 c, 0;\nLAB_WAIT:\nmbarrier.try_wait.parity.shared::cta.b64 p, [%0], %1;\n@p bra LAB_DONE;\n"
                 "add.u32 c, c, 1;\nsetp.lt.u32 p, c, 4194304;\n@p bra LAB_WAIT;\ntrap;\nLAB_DONE:\n}\n" :: "r"(bar), "r"(parity) : "memory");
}
__device__ __forceinline__ void mbar_wait_long(uint32_t bar, uint32_t parity) {
    asm volatile("{\n.reg .pred p;\n.reg .u32 c;\nmov.u32 c, 0;\nLAB_WAIT:\nmbarrier.try_wait.parity.shared::cta.b64 p, [%0], %1, 100000;\n@p bra LAB_DONE;\n"
                 "add.u32 c, c, 1;\nsetp.lt.u32 p, c, 262144;\n@p bra LAB_WAIT;\ntrap;\nLAB_DONE:\n}\n" :: "r"(bar), "r"(parity) : "memory");
}
__device__ __forceinline__ void flag_wait(const unsigned int* cnt, unsigned int target) {
    asm volatile("{\n.reg .pred p;\n.reg .u32 c, v;\nmov.u32 c, 0;\nLAB_WAIT:\nld.acquire.gpu.global.u32 v, [%0];\nsub.u32 v, v, %1;\nsetp.ge.s32 p, v, 0;\n@p bra LAB_DONE;\n"
                 "nanosleep.u32 64;\nadd.u32 c, c, 1;\nsetp.lt.u32 p, c, 4194304;\n@p bra LAB_WAIT;\ntrap;\nLAB_DONE:\n}\n" :: "l"(cnt), "r"(target) : "memory");
}
__device__ __forceinline__ void flag_signal(unsigned int* cnt) {
    asm volatile("red.release.gpu.global.add.u32 [%0], 1;" :: "l"(cnt) : "memory");
}
__device__ __forceinline__ void flag_signal_relaxed(unsigned int* cnt) {
    asm volatile("red.relaxed.gpu.global.add.u32 [%0], 1;" :: "l"(cnt) : "memory");
}
__device__ __forceinline__ void tma2d(uint32_t dst, const CUtensorMap* m, int c0, int c1, uint32_t bar) {
    asm volatile("cp.async.bulk.tensor.2d.shared::cluster.global.mbarrier::complete_tx::bytes [%0], [%1, {%3, %4}], [%2];"
                 :: "r"(dst), "l"(m), "r"(bar), "r"(c0), "r"(c1) : "memory");
}
__device__ __forceinline__ void tma3d(uint32_t dst, const CUtensorMap* m, int c0, int c1, int c2, uint32_t bar) {
    asm volatile("cp.async.bulk.tensor.3d.shared::cluster.global.mbarrier::complete_tx::bytes [%0], [%1, {%3, %4, %5}], [%2];"
                 :: "r"(dst), "l"(m), "r"(bar), "r"(c0), "r"(c1), "r"(c2) : "memory");
}
__device__ __forceinline__ void tma5d(uint32_t dst, const CUtensorMap* m, int c0, int c1, int c2, int c3, int c4, uint32_t bar) {
    asm volatile("cp.async.bulk.tensor.5d.shared::cluster.global.mbarrier::complete_tx::bytes [%0], [%1, {%3, %4, %5, %6, %7}], [%2];"
                 :: "r"(dst), "l"(m), "r"(bar), "r"(c0), "r"(c1), "r"(c2), "r"(c3), "r"(c4) : "memory");
}
__device__ __forceinline__ bool elect_one() {
    uint32_t p;
    asm volatile("{\n.reg .pred P;\nelect.sync _|P, 0xffffffff;\nselp.u32 %0, 1, 0, P;\n}\n" : "=r"(p));
    return p != 0;
}
__device__ __forceinline__ void prefetch_map(const CUtensorMap* m) { asm volatile("prefetch.tensormap [%0];" :: "l"(m) : "memory"); }
__device__ __forceinline__ void tma2d_store(const CUtensorMap* m, uint32_t src, int c0, int c1) {
    asm volatile("cp.async.bulk.tensor.2d.global.shared::cta.bulk_group [%0, {%2, %3}], [%1];" :: "l"(m), "r"(src), "r"(c0), "r"(c1) : "memory");
}
__device__ __forceinline__ void bulk_load(uint32_t dst, const void* src, uint32_t bytes, uint32_t bar) {
    asm volatile("cp.async.bulk.shared::cluster.global.mbarrier::complete_tx::bytes [%0], [%1], %2, [%3];" :: "r"(dst), "l"(src), "r"(bytes), "r"(bar) : "memory");
}
__device__ __forceinline__ void bulk_store(void* dst, uint32_t src, uint32_t bytes) {
    asm volatile("cp.async.bulk.global.shared::cta.bulk_group [%0], [%1], %2;" :: "l"(dst), "r"(src), "r"(bytes) : "memory");
}
__device__ __forceinline__ void bulk_commit() { asm volatile("cp.async.bulk.commit_group;" ::: "memory"); }
__device__ __forceinline__ void bulk_wait_all() { asm volatile("cp.async.bulk.wait_group 0;" ::: "memory"); }
__device__ __forceinline__ void fence_async_smem() { asm volatile("fence.proxy.async.shared::cta;" ::: "memory"); }
__device__ __forceinline__ void fence_async_all() { asm volatile("fence.proxy.async;" ::: "memory"); }
__device__ __forceinline__ void wg_fence() { asm volatile("wgmma.fence.sync.aligned;" ::: "memory"); }
__device__ __forceinline__ void wg_commit() { asm volatile("wgmma.commit_group.sync.aligned;" ::: "memory"); }
template <int N> __device__ __forceinline__ void wg_wait() { asm volatile("wgmma.wait_group.sync.aligned %0;" :: "n"(N) : "memory"); }
__device__ __forceinline__ void bar_sync(int id, int n) { asm volatile("bar.sync %0, %1;" :: "r"(id), "r"(n) : "memory"); }
template <int N> __device__ __forceinline__ void reg_alloc() { asm volatile("setmaxnreg.inc.sync.aligned.u32 %0;" :: "n"(N)); }
template <int N> __device__ __forceinline__ void reg_dealloc() { asm volatile("setmaxnreg.dec.sync.aligned.u32 %0;" :: "n"(N)); }
__device__ __forceinline__ void stsm4(uint32_t addr, uint32_t r0, uint32_t r1, uint32_t r2, uint32_t r3) {
    asm volatile("stmatrix.sync.aligned.m8n8.x4.shared.b16 [%0], {%1, %2, %3, %4};" :: "r"(addr), "r"(r0), "r"(r1), "r"(r2), "r"(r3) : "memory");
}
__device__ __forceinline__ void stsm4_t(uint32_t addr, uint32_t r0, uint32_t r1, uint32_t r2, uint32_t r3) {
    asm volatile("stmatrix.sync.aligned.m8n8.x4.trans.shared.b16 [%0], {%1, %2, %3, %4};" :: "r"(addr), "r"(r0), "r"(r1), "r"(r2), "r"(r3) : "memory");
}
__host__ __device__ constexpr uint64_t desc_hi(uint32_t lbo, uint32_t sbo, int swz) {
    return ((uint64_t)((lbo & 0x3FFFF) >> 4) << 16) | ((uint64_t)((sbo & 0x3FFFF) >> 4) << 32) | ((uint64_t)swz << 62);
}
__device__ __forceinline__ uint64_t desc_lo(uint32_t addr) { return (uint64_t)((addr & 0x3FFFF) >> 4); }
constexpr uint64_t D_K128 = desc_hi(16, 1024, 1);
constexpr uint64_t D_K64 = desc_hi(16, 512, 2);
__device__ __forceinline__ uint32_t pack_bf16(float lo, float hi) {
    uint32_t r; asm("cvt.rn.bf16x2.f32 %0, %1, %2;" : "=r"(r) : "f"(hi), "f"(lo)); return r;
}
__device__ __forceinline__ float bf_lo(uint32_t r) { return __uint_as_float(r << 16); }
__device__ __forceinline__ float bf_hi(uint32_t r) { return __uint_as_float(r & 0xFFFF0000u); }
__device__ __forceinline__ float bf_round(float x) { return __bfloat162float(__float2bfloat16_rn(x)); }
__device__ __forceinline__ float ex2(float x) { float y; asm("ex2.approx.ftz.f32 %0, %1;" : "=f"(y) : "f"(x)); return y; }
template <int R> __device__ __forceinline__ void fence_regs(float (&d)[R]) {
    #pragma unroll
    for (int i = 0; i < R; i++) asm volatile("" : "+f"(d[i]) :: "memory");
}
template <int R> __device__ __forceinline__ void fence_regs(uint32_t (&d)[R]) {
    #pragma unroll
    for (int i = 0; i < R; i++) asm volatile("" : "+r"(d[i]) :: "memory");
}
__device__ __forceinline__ void quad_transpose(uint32_t (&r)[4], int t) {
    uint32_t s0 = (t & 1) ? r[0] : r[1], s1 = (t & 1) ? r[2] : r[3];
    s0 = __shfl_xor_sync(0xffffffffu, s0, 1); s1 = __shfl_xor_sync(0xffffffffu, s1, 1);
    if (t & 1) { r[0] = s0; r[2] = s1; } else { r[1] = s0; r[3] = s1; }
    s0 = (t & 2) ? r[0] : r[2]; s1 = (t & 2) ? r[1] : r[3];
    s0 = __shfl_xor_sync(0xffffffffu, s0, 2); s1 = __shfl_xor_sync(0xffffffffu, s1, 2);
    if (t & 2) { r[0] = s0; r[1] = s1; } else { r[2] = s0; r[3] = s1; }
}
template <int R> __device__ __forceinline__ void pack32(const float (&a)[R], int b0, int rr, float scale, uint32_t (&r)[4]) {
    #pragma unroll
    for (int b = 0; b < 4; b++) r[b] = pack_bf16(a[4 * (b0 + b) + 2 * rr] * scale, a[4 * (b0 + b) + 2 * rr + 1] * scale);
}
__device__ __forceinline__ float sumsq4(const uint32_t (&r)[4]) {
    float s = 0.f;
    #pragma unroll
    for (int b = 0; b < 4; b++) { float lo = bf_lo(r[b]), hi = bf_hi(r[b]); s = fmaf(lo, lo, s); s = fmaf(hi, hi, s); }
    s += __shfl_xor_sync(0xffffffffu, s, 1); s += __shfl_xor_sync(0xffffffffu, s, 2);
    return s;
}

__device__ __forceinline__ void wg_ss_n192_tb(float (&d)[96], uint64_t da, uint64_t db, int sd) {
    asm volatile("{\n.reg .pred p;\nsetp.ne.b32 p, %98, 0;\n"
        "wgmma.mma_async.sync.aligned.m64n192k16.f32.bf16.bf16 {"
        "%0, %1, %2, %3, %4, %5, %6, %7, %8, %9, %10, %11, %12, %13, %14, %15, "
        "%16, %17, %18, %19, %20, %21, %22, %23, %24, %25, %26, %27, %28, %29, %30, %31, "
        "%32, %33, %34, %35, %36, %37, %38, %39, %40, %41, %42, %43, %44, %45, %46, %47, "
        "%48, %49, %50, %51, %52, %53, %54, %55, %56, %57, %58, %59, %60, %61, %62, %63, "
        "%64, %65, %66, %67, %68, %69, %70, %71, %72, %73, %74, %75, %76, %77, %78, %79, "
        "%80, %81, %82, %83, %84, %85, %86, %87, %88, %89, %90, %91, %92, %93, %94, %95}, %96, %97, p, 1, 1, 0, 1;\n}\n"
        : "+f"(d[0]), "+f"(d[1]), "+f"(d[2]), "+f"(d[3]), "+f"(d[4]), "+f"(d[5]), "+f"(d[6]), "+f"(d[7]),
          "+f"(d[8]), "+f"(d[9]), "+f"(d[10]), "+f"(d[11]), "+f"(d[12]), "+f"(d[13]), "+f"(d[14]), "+f"(d[15]),
          "+f"(d[16]), "+f"(d[17]), "+f"(d[18]), "+f"(d[19]), "+f"(d[20]), "+f"(d[21]), "+f"(d[22]), "+f"(d[23]),
          "+f"(d[24]), "+f"(d[25]), "+f"(d[26]), "+f"(d[27]), "+f"(d[28]), "+f"(d[29]), "+f"(d[30]), "+f"(d[31]),
          "+f"(d[32]), "+f"(d[33]), "+f"(d[34]), "+f"(d[35]), "+f"(d[36]), "+f"(d[37]), "+f"(d[38]), "+f"(d[39]),
          "+f"(d[40]), "+f"(d[41]), "+f"(d[42]), "+f"(d[43]), "+f"(d[44]), "+f"(d[45]), "+f"(d[46]), "+f"(d[47]),
          "+f"(d[48]), "+f"(d[49]), "+f"(d[50]), "+f"(d[51]), "+f"(d[52]), "+f"(d[53]), "+f"(d[54]), "+f"(d[55]),
          "+f"(d[56]), "+f"(d[57]), "+f"(d[58]), "+f"(d[59]), "+f"(d[60]), "+f"(d[61]), "+f"(d[62]), "+f"(d[63]),
          "+f"(d[64]), "+f"(d[65]), "+f"(d[66]), "+f"(d[67]), "+f"(d[68]), "+f"(d[69]), "+f"(d[70]), "+f"(d[71]),
          "+f"(d[72]), "+f"(d[73]), "+f"(d[74]), "+f"(d[75]), "+f"(d[76]), "+f"(d[77]), "+f"(d[78]), "+f"(d[79]),
          "+f"(d[80]), "+f"(d[81]), "+f"(d[82]), "+f"(d[83]), "+f"(d[84]), "+f"(d[85]), "+f"(d[86]), "+f"(d[87]),
          "+f"(d[88]), "+f"(d[89]), "+f"(d[90]), "+f"(d[91]), "+f"(d[92]), "+f"(d[93]), "+f"(d[94]), "+f"(d[95])
        : "l"(da), "l"(db), "r"(sd));
}
__device__ __forceinline__ void wg_ss_n128_tb(float (&d)[64], uint64_t da, uint64_t db, int sd) {
    asm volatile("{\n.reg .pred p;\nsetp.ne.b32 p, %66, 0;\n"
        "wgmma.mma_async.sync.aligned.m64n128k16.f32.bf16.bf16 {"
        "%0, %1, %2, %3, %4, %5, %6, %7, %8, %9, %10, %11, %12, %13, %14, %15, "
        "%16, %17, %18, %19, %20, %21, %22, %23, %24, %25, %26, %27, %28, %29, %30, %31, "
        "%32, %33, %34, %35, %36, %37, %38, %39, %40, %41, %42, %43, %44, %45, %46, %47, "
        "%48, %49, %50, %51, %52, %53, %54, %55, %56, %57, %58, %59, %60, %61, %62, %63}, %64, %65, p, 1, 1, 0, 1;\n}\n"
        : "+f"(d[0]), "+f"(d[1]), "+f"(d[2]), "+f"(d[3]), "+f"(d[4]), "+f"(d[5]), "+f"(d[6]), "+f"(d[7]),
          "+f"(d[8]), "+f"(d[9]), "+f"(d[10]), "+f"(d[11]), "+f"(d[12]), "+f"(d[13]), "+f"(d[14]), "+f"(d[15]),
          "+f"(d[16]), "+f"(d[17]), "+f"(d[18]), "+f"(d[19]), "+f"(d[20]), "+f"(d[21]), "+f"(d[22]), "+f"(d[23]),
          "+f"(d[24]), "+f"(d[25]), "+f"(d[26]), "+f"(d[27]), "+f"(d[28]), "+f"(d[29]), "+f"(d[30]), "+f"(d[31]),
          "+f"(d[32]), "+f"(d[33]), "+f"(d[34]), "+f"(d[35]), "+f"(d[36]), "+f"(d[37]), "+f"(d[38]), "+f"(d[39]),
          "+f"(d[40]), "+f"(d[41]), "+f"(d[42]), "+f"(d[43]), "+f"(d[44]), "+f"(d[45]), "+f"(d[46]), "+f"(d[47]),
          "+f"(d[48]), "+f"(d[49]), "+f"(d[50]), "+f"(d[51]), "+f"(d[52]), "+f"(d[53]), "+f"(d[54]), "+f"(d[55]),
          "+f"(d[56]), "+f"(d[57]), "+f"(d[58]), "+f"(d[59]), "+f"(d[60]), "+f"(d[61]), "+f"(d[62]), "+f"(d[63])
        : "l"(da), "l"(db), "r"(sd));
}
__device__ __forceinline__ void wg_ss_n64(float (&d)[32], uint64_t da, uint64_t db, int sd) {
    asm volatile("{\n.reg .pred p;\nsetp.ne.b32 p, %34, 0;\n"
        "wgmma.mma_async.sync.aligned.m64n64k16.f32.bf16.bf16 {"
        "%0, %1, %2, %3, %4, %5, %6, %7, %8, %9, %10, %11, %12, %13, %14, %15, "
        "%16, %17, %18, %19, %20, %21, %22, %23, %24, %25, %26, %27, %28, %29, %30, %31}, %32, %33, p, 1, 1, 0, 0;\n}\n"
        : "+f"(d[0]), "+f"(d[1]), "+f"(d[2]), "+f"(d[3]), "+f"(d[4]), "+f"(d[5]), "+f"(d[6]), "+f"(d[7]),
          "+f"(d[8]), "+f"(d[9]), "+f"(d[10]), "+f"(d[11]), "+f"(d[12]), "+f"(d[13]), "+f"(d[14]), "+f"(d[15]),
          "+f"(d[16]), "+f"(d[17]), "+f"(d[18]), "+f"(d[19]), "+f"(d[20]), "+f"(d[21]), "+f"(d[22]), "+f"(d[23]),
          "+f"(d[24]), "+f"(d[25]), "+f"(d[26]), "+f"(d[27]), "+f"(d[28]), "+f"(d[29]), "+f"(d[30]), "+f"(d[31])
        : "l"(da), "l"(db), "r"(sd));
}
__device__ __forceinline__ void wg_rs_n40(float (&d)[20], uint32_t a0, uint32_t a1, uint32_t a2, uint32_t a3, uint64_t db, int sd) {
    asm volatile("{\n.reg .pred p;\nsetp.ne.b32 p, %25, 0;\n"
        "wgmma.mma_async.sync.aligned.m64n40k16.f32.bf16.bf16 {"
        "%0, %1, %2, %3, %4, %5, %6, %7, %8, %9, %10, %11, %12, %13, %14, %15, "
        "%16, %17, %18, %19}, {%20, %21, %22, %23}, %24, p, 1, 1, 0;\n}\n"
        : "+f"(d[0]), "+f"(d[1]), "+f"(d[2]), "+f"(d[3]), "+f"(d[4]), "+f"(d[5]), "+f"(d[6]), "+f"(d[7]),
          "+f"(d[8]), "+f"(d[9]), "+f"(d[10]), "+f"(d[11]), "+f"(d[12]), "+f"(d[13]), "+f"(d[14]), "+f"(d[15]),
          "+f"(d[16]), "+f"(d[17]), "+f"(d[18]), "+f"(d[19])
        : "r"(a0), "r"(a1), "r"(a2), "r"(a3), "l"(db), "r"(sd));
}
__device__ __forceinline__ void wg_rs_n32(float (&d)[16], uint32_t a0, uint32_t a1, uint32_t a2, uint32_t a3, uint64_t db, int sd) {
    asm volatile("{\n.reg .pred p;\nsetp.ne.b32 p, %21, 0;\n"
        "wgmma.mma_async.sync.aligned.m64n32k16.f32.bf16.bf16 {"
        "%0, %1, %2, %3, %4, %5, %6, %7, %8, %9, %10, %11, %12, %13, %14, %15}, {%16, %17, %18, %19}, %20, p, 1, 1, 0;\n}\n"
        : "+f"(d[0]), "+f"(d[1]), "+f"(d[2]), "+f"(d[3]), "+f"(d[4]), "+f"(d[5]), "+f"(d[6]), "+f"(d[7]),
          "+f"(d[8]), "+f"(d[9]), "+f"(d[10]), "+f"(d[11]), "+f"(d[12]), "+f"(d[13]), "+f"(d[14]), "+f"(d[15])
        : "r"(a0), "r"(a1), "r"(a2), "r"(a3), "l"(db), "r"(sd));
}
__device__ __forceinline__ void wg_ss_n40_ta(float (&d)[20], uint64_t da, uint64_t db, int sd) {
    asm volatile("{\n.reg .pred p;\nsetp.ne.b32 p, %22, 0;\n"
        "wgmma.mma_async.sync.aligned.m64n40k16.f32.bf16.bf16 {"
        "%0, %1, %2, %3, %4, %5, %6, %7, %8, %9, %10, %11, %12, %13, %14, %15, "
        "%16, %17, %18, %19}, %20, %21, p, 1, 1, 1, 0;\n}\n"
        : "+f"(d[0]), "+f"(d[1]), "+f"(d[2]), "+f"(d[3]), "+f"(d[4]), "+f"(d[5]), "+f"(d[6]), "+f"(d[7]),
          "+f"(d[8]), "+f"(d[9]), "+f"(d[10]), "+f"(d[11]), "+f"(d[12]), "+f"(d[13]), "+f"(d[14]), "+f"(d[15]),
          "+f"(d[16]), "+f"(d[17]), "+f"(d[18]), "+f"(d[19])
        : "l"(da), "l"(db), "r"(sd));
}

__device__ __forceinline__ float acc_sumsq(const float (&a)[96], int b0, int rr) {
    float s = 0.f;
    #pragma unroll
    for (int b = 0; b < 4; b++) { s = fmaf(a[4 * (b0 + b) + 2 * rr], a[4 * (b0 + b) + 2 * rr], s); s = fmaf(a[4 * (b0 + b) + 2 * rr + 1], a[4 * (b0 + b) + 2 * rr + 1], s); }
    return s;
}
__device__ __forceinline__ float quad_norms(const float (&a)[96], int X, int t) {
    const float p0 = acc_sumsq(a, X * 8, 0), p1 = acc_sumsq(a, X * 8, 1), p2 = acc_sumsq(a, X * 8 + 4, 0), p3 = acc_sumsq(a, X * 8 + 4, 1);
    const float k0 = (t & 1) ? p1 : p0, s0 = (t & 1) ? p0 : p1, k1 = (t & 1) ? p3 : p2, s1 = (t & 1) ? p2 : p3;
    const float u0 = k0 + __shfl_xor_sync(0xffffffffu, s0, 1), u1 = k1 + __shfl_xor_sync(0xffffffffu, s1, 1);
    return ((t & 2) ? u1 : u0) + __shfl_xor_sync(0xffffffffu, (t & 2) ? u0 : u1, 2);
}
__device__ __forceinline__ void publish_norm(float v, int X, uint8_t* sp, int lane) {
    v = fmaxf(v, __shfl_xor_sync(0xffffffffu, v, 1));
    v = fmaxf(v, __shfl_xor_sync(0xffffffffu, v, 4)); v = fmaxf(v, __shfl_xor_sync(0xffffffffu, v, 8)); v = fmaxf(v, __shfl_xor_sync(0xffffffffu, v, 16));
    if ((lane & ~2) == 0) atomicMax((unsigned int*)(sp + NORM_OFF) + X * 2 + (lane >> 1), __float_as_uint(v * (X == 0 ? 1.02f * 0.0650428f : 1.02f)));
}
template <int X>
__device__ __forceinline__ void p1_store_rows(const float (&a)[96], int m, int wg, int w4, int lane, uint32_t sb) {
    const float QS = 0.17677669529663687f * 1.4426950408889634f;
    const int mat = lane >> 3, i = lane & 7;
    #pragma unroll
    for (int hh = 0; hh < 2; hh++) {
        uint32_t vl[4], vh[4];
        pack32(a, X * 8 + hh * 4, 0, X == 0 ? QS : 1.f, vl);
        pack32(a, X * 8 + hh * 4, 1, X == 0 ? QS : 1.f, vh);
        const int row = m * 64 + w4 * 16 + (mat & 1) * 8 + i;
        const uint32_t base = (X == 0 ? sb + Q_OFF + hh * 16384 + wg * 8192 : sb + KV_OFF + (hh * 2 + wg) * KV_STAGE) + row * 64;
        #pragma unroll
        for (int bp = 0; bp < 2; bp++)
            stsm4(base + (((2 * bp + (mat >> 1)) ^ ((row >> 1) & 3)) << 4), vl[2 * bp], vh[2 * bp], vl[2 * bp + 1], vh[2 * bp + 1]);
    }
}
__device__ __forceinline__ void p1_store_vt(const float (&a)[96], int m, int wg, int w4, int lane, uint32_t sb) {
    const int mat = lane >> 3, i = lane & 7;
    #pragma unroll
    for (int hh = 0; hh < 2; hh++) {
        uint32_t vl[4], vh[4];
        pack32(a, 16 + hh * 4, 0, 1.f, vl);
        pack32(a, 16 + hh * 4, 1, 1.f, vh);
        const uint32_t base = sb + KV_OFF + (hh * 2 + wg) * KV_STAGE + 8192 + m * 5120;
        #pragma unroll
        for (int bp = 0; bp < 2; bp++) {
            const int rowd = 8 * (2 * bp + (mat >> 1)) + i, chunk = 2 * w4 + (mat & 1);
            stsm4_t(base + rowd * 128 + ((chunk ^ i) << 4), vl[2 * bp], vh[2 * bp], vl[2 * bp + 1], vh[2 * bp + 1]);
        }
    }
}

__device__ __forceinline__ void phase1(uint32_t sb, uint8_t* sp, int wg, int w4, int lane, long long t0) {
    const uint32_t bars = sb + BAR_OFF;
    const bool elect = (w4 == 0 && lane == 0);
    float a0[96], a1[96];
    #pragma unroll 1
    for (int ks = 0; ks < 16; ks++) {
        const int s = ks % R1_N;
        mbar_wait(bars + (B_FULL1 + s) * 8, (ks / R1_N) & 1);
        if (wg == 0 && ks == 0 && w4 == 0 && lane == 0) GT1(3);
        if (wg == 0 && (ks == 0 || ks == 1 || ks == 8)) ASTAMP(13 + (ks == 0 ? 0 : ks == 1 ? 1 : 2));
        const uint32_t st = sb + s * R1_STAGE;
        const uint64_t da = D_K128 | desc_lo(st + wg * 16384);
        const uint64_t db = desc_hi(8192, 1024, 1) | desc_lo(st + R1_A);
        wg_fence();
        #pragma unroll
        for (int k = 0; k < 4; k++) {
            wg_ss_n192_tb(a0, da + k * 2, db + k * 128, (ks > 0 || k > 0) ? 1 : 0);
            wg_ss_n192_tb(a1, da + 512 + k * 2, db + k * 128, (ks > 0 || k > 0) ? 1 : 0);
        }
        wg_commit();
        wg_wait<0>();
        mbar_arrive_if(bars + (B_EMPTY1 + s) * 8, elect);
    }
    fence_regs(a0); fence_regs(a1);
    bar_sync(3, 256);
    const int tid = wg * 128 + w4 * 32 + lane;
    if (tid == 0) mbar_arrive(bars + B_R1FREE * 8);
    if (wg == 0) STAMP(0);
    const int t = lane & 3;
    p1_store_rows<1>(a0, 0, wg, w4, lane, sb); p1_store_vt(a0, 0, wg, w4, lane, sb);
    p1_store_rows<1>(a1, 1, wg, w4, lane, sb); p1_store_vt(a1, 1, wg, w4, lane, sb);
    fence_async_smem();
    publish_norm(fmaxf(quad_norms(a0, 1, t), quad_norms(a1, 1, t)), 1, sp, lane);
    publish_norm(fmaxf(quad_norms(a0, 2, t), quad_norms(a1, 2, t)), 2, sp, lane);
    bar_sync(3, 256);
    if (tid == 0) mbar_arrive(bars + B_KVSTAGED * 8);
    p1_store_rows<0>(a0, 0, wg, w4, lane, sb);
    p1_store_rows<0>(a1, 1, wg, w4, lane, sb);
    fence_async_smem();
    publish_norm(fmaxf(quad_norms(a0, 0, t), quad_norms(a1, 0, t)), 0, sp, lane);
    bar_sync(3, 256);
    if (tid == 0) mbar_arrive(bars + B_P1DONE * 8);
    if (wg == 0) STAMP(1);
}

#define HEADP 3
#define POLYMASK 0
__device__ __forceinline__ float exp2_fma(float x) {
    const float MAGIC = 12582912.f;
    const float t = __fadd_rn(x, MAGIC);
    const float f = __fadd_rn(x, -__fadd_rn(t, -MAGIC));
    float p = fmaf(0.0551716685295105f, f, 0.2426111251115799f);
    p = fmaf(p, f, 0.6932609677314758f);
    p = fmaf(p, f, 0.9999280571937561f);
    return __uint_as_float(__float_as_uint(p) + (__float_as_uint(t) << 23));
}
__device__ __forceinline__ void exp_pack(const float (&s)[32], uint32_t (&p)[16]) {
    #pragma unroll
    for (int i = 0; i < 16; i++) {
        const float e0 = ((POLYMASK >> ((2 * i) & 15)) & 1) ? exp2_fma(s[2 * i]) : ex2(s[2 * i]);
        const float e1 = ((POLYMASK >> ((2 * i + 1) & 15)) & 1) ? exp2_fma(s[2 * i + 1]) : ex2(s[2 * i + 1]);
        p[i] = pack_bf16(e0, e1);
    }
}
template <int I0, int I1>
__device__ __forceinline__ void exp_pack_part(const float (&s)[32], uint32_t (&p)[16]) {
    #pragma unroll
    for (int i = I0; i < I1; i++) {
        float e0, e1;
        asm volatile("ex2.approx.ftz.f32 %0, %1;" : "=f"(e0) : "f"(s[2 * i]));
        asm volatile("ex2.approx.ftz.f32 %0, %1;" : "=f"(e1) : "f"(s[2 * i + 1]));
        p[i] = pack_bf16(e0, e1);
    }
}
__device__ __forceinline__ void qk_issue(float (&s)[32], uint64_t dq, uint64_t dk) {
    wg_ss_n64(s, dq, dk, 0);
    wg_ss_n64(s, dq + 2, dk + 2, 1);
}
__device__ __forceinline__ void pv_issue(float (&o)[20], const uint32_t (&p)[16], uint64_t dv) {
    #pragma unroll
    for (int k = 0; k < 4; k++) wg_rs_n40(o, p[4 * k], p[4 * k + 1], p[4 * k + 2], p[4 * k + 3], dv + 2 * k, 1);
}
__device__ __forceinline__ void online_exp_pack(float (&s)[32], uint32_t (&p)[16], float (&o)[20], float (&mx)[2]) {
    #pragma unroll
    for (int rr = 0; rr < 2; rr++) {
        float m = mx[rr];
        #pragma unroll
        for (int b = 0; b < 8; b++) m = fmaxf(m, fmaxf(s[4 * b + 2 * rr], s[4 * b + 2 * rr + 1]));
        m = fmaxf(m, __shfl_xor_sync(0xffffffffu, m, 1)); m = fmaxf(m, __shfl_xor_sync(0xffffffffu, m, 2));
        const float sc = ex2(mx[rr] - m);
        mx[rr] = m;
        #pragma unroll
        for (int b = 0; b < 5; b++) { o[4 * b + 2 * rr] *= sc; o[4 * b + 2 * rr + 1] *= sc; }
        #pragma unroll
        for (int b = 0; b < 8; b++) p[2 * b + rr] = pack_bf16(ex2(s[4 * b + 2 * rr] - m), ex2(s[4 * b + 2 * rr + 1] - m));
    }
}
__device__ __forceinline__ void attn_stage(const float (&o)[20], uint32_t base, int w4, int lane) {
    uint32_t vl[4], vh[4];
    pack32(o, 0, 0, 1.f / __shfl_sync(0xffffffffu, o[16], lane & ~3), vl);
    pack32(o, 0, 1, 1.f / __shfl_sync(0xffffffffu, o[18], lane & ~3), vh);
    const int mat = lane >> 3, row = w4 * 16 + (mat & 1) * 8 + (lane & 7);
    #pragma unroll
    for (int bp = 0; bp < 2; bp++)
        stsm4(base + row * 64 + (((2 * bp + (mat >> 1)) ^ ((row >> 1) & 3)) << 4), vl[2 * bp], vh[2 * bp], vl[2 * bp + 1], vh[2 * bp + 1]);
}

__device__ __forceinline__ bool scores_bounded(float nq, float nk, float nv) {
    return (nq * nk <= 3600.f) && (nv <= 1e24f) && (nq <= 1e18f) && (nk <= 1e18f);
}
__device__ __forceinline__ void attention(uint32_t sb, uint8_t* sp, int wg, int w4, int lane, long long t0) {
    const uint32_t bars = sb + BAR_OFF;
    const bool elect = (w4 == 0 && lane == 0);
    const volatile float* nloc = (const volatile float*)(sp + NORM_OFF);
    #pragma unroll 1
    for (int task = 0; task < 2; task++) {
        bool fast = true;
        if (task == 0) fast = scores_bounded(nloc[0], nloc[2], nloc[4]);
        const uint64_t dqa = D_K64 | desc_lo(sb + Q_OFF + task * 16384 + wg * 8192), dqb = dqa + 256;
        float oa[20], ob[20], sa[32], sc[32];
        uint32_t pa[16], pb[16];
        #pragma unroll
        for (int i = 0; i < 20; i++) { oa[i] = 0.f; ob[i] = 0.f; }
        fence_regs(oa); fence_regs(ob);
        const uint64_t dkb = D_K64 | desc_lo(sb + KV_OFF), dvb = D_K128 | desc_lo(sb + KV_OFF + 8192);
        int body = 0;
        #pragma unroll 1
        for (; body < 8; body++) {
            if (body == (task == 0 ? 1 : 0)) {
                if (task == 0 && wg == 0) ASTAMP(12);
                mbar_wait(bars + B_NORMOK * 8, 0);
                fast = fast && ((*((const volatile unsigned int*)(sp + NORM_OFF) + 8) >> task) & 1u);
            }
            if (!fast) break;
            if (task == 0 && body == 1 && wg == 0) STAMP(2);
            const int s0 = (body & 1) * 2;
            const uint32_t par = (task * 4 + (body >> 1)) & 1;
            const uint64_t dk0 = dkb + s0 * (KV_STAGE >> 4), dv0 = dvb + s0 * (KV_STAGE >> 4);
            mbar_wait(bars + (B_KVFULL + s0) * 8, par);
            wg_fence();
            qk_issue(sa, dqa, dk0); wg_commit();
            qk_issue(sc, dqb, dk0); wg_commit();
            #pragma unroll
            for (int q = 0; q < 4; q++) {
                const int u = q >> 1, half = q & 1, qn = q + 1;
                const uint64_t dv = dv0 + u * (KV_STAGE >> 4) + half * (5120 >> 4);
                const uint64_t dkn = dk0 + (qn >> 1) * (KV_STAGE >> 4) + (qn & 1) * (4096 >> 4);
                wg_wait<1>();
                fence_regs(sa);
                exp_pack(sa, pa);
                if (q == 1) mbar_wait(bars + (B_KVFULL + s0 + 1) * 8, par);
                fence_regs(pa);
                wg_fence();
                pv_issue(oa, pa, dv);
                if (qn < 4) qk_issue(sa, dqa, dkn);
                wg_commit();
                wg_wait<1>();
                fence_regs(sc);
                if (q == 2) mbar_arrive_if(bars + (B_KVEMPTY + s0) * 8, elect);
                exp_pack(sc, pb);
                fence_regs(pb);
                wg_fence();
                pv_issue(ob, pb, dv);
                if (qn < 4) qk_issue(sc, dqb, dkn);
                wg_commit();
            }
            wg_wait<0>();
            fence_regs(oa); fence_regs(ob);
            mbar_arrive_if(bars + (B_KVEMPTY + s0 + 1) * 8, elect);
        }
        if (body < 8) {
            const float m0 = body > 0 ? 0.f : -INFINITY;
            float ma[2] = {m0, m0}, mb[2] = {m0, m0};
            #pragma unroll 1
            for (int q = body * 4; q < 32; q++) {
                const int u = (q >> 1) & 3, half = q & 1;
                const uint32_t par = (task * 4 + (q >> 3)) & 1;
                if (half == 0) mbar_wait(bars + (B_KVFULL + u) * 8, par);
                const uint64_t dk = dkb + u * (KV_STAGE >> 4) + half * (4096 >> 4);
                const uint64_t dv = dvb + u * (KV_STAGE >> 4) + half * (5120 >> 4);
                wg_fence();
                qk_issue(sa, dqa, dk);
                qk_issue(sc, dqb, dk);
                wg_commit();
                wg_wait<0>();
                fence_regs(sa); fence_regs(sc);
                online_exp_pack(sa, pa, oa, ma);
                online_exp_pack(sc, pb, ob, mb);
                fence_regs(pa); fence_regs(pb); fence_regs(oa); fence_regs(ob);
                wg_fence();
                pv_issue(oa, pa, dv);
                pv_issue(ob, pb, dv);
                wg_commit();
                wg_wait<0>();
                fence_regs(oa); fence_regs(ob);
                if (half == 1) mbar_arrive_if(bars + (B_KVEMPTY + u) * 8, elect);
            }
        }
        attn_stage(oa, sb + Q_OFF + task * 16384 + wg * 8192, w4, lane);
        attn_stage(ob, sb + Q_OFF + task * 16384 + wg * 8192 + 4096, w4, lane);
        fence_async_smem();
        __syncwarp();
        mbar_arrive_if(bars + (B_ODONE + wg) * 8, lane == 0);
        if (wg == 0) STAMP(3 + task);
    }
}

__device__ __forceinline__ void phase3(uint32_t sb, int wg, int w4, int lane, int c, const Params& P, long long t0) {
    const uint32_t bars = sb + BAR_OFF;
    const bool elect = (w4 == 0 && lane == 0);
    float a0[64], a1[64];
    #pragma unroll 1
    for (int ks = 0; ks < 16; ks++) {
        const int s = ks & 3;
        mbar_wait(bars + (B_FULL3 + s) * 8, (ks >> 2) & 1);
        if (wg == 0 && ks == 0) STAMP(5);
        const uint32_t st = sb + s * R3_STAGE;
        const uint64_t da = D_K128 | desc_lo(st + wg * 8192);
        const uint64_t db = desc_hi(8192, 1024, 1) | desc_lo(st + R3_A);
        wg_fence();
        #pragma unroll
        for (int k = 0; k < 4; k++) {
            wg_ss_n128_tb(a0, da + k * 2, db + k * 128, (ks > 0 || k > 0) ? 1 : 0);
            wg_ss_n128_tb(a1, da + k * 2, db + 1024 + k * 128, (ks > 0 || k > 0) ? 1 : 0);
        }
        wg_commit();
        wg_wait<0>();
        mbar_arrive_if(bars + (B_EMPTY3 + s) * 8, elect);
    }
    fence_regs(a0); fence_regs(a1);
    if (wg == 0) STAMP(6);
    const int br = c >> 6, rb = c & 15, cb = (c >> 4) & 3;
    bar_sync(3, 256);
    const uint32_t stg = sb + wg * 32768;
    const int mat = lane >> 3, row = w4 * 16 + (mat & 1) * 8 + (lane & 7);
    #pragma unroll
    for (int g = 0; g < 4; g++) {
        #pragma unroll
        for (int bp = 0; bp < 4; bp++) {
            const int b = (g & 1) * 8 + 2 * bp;
            const uint32_t ad = stg + g * 8192 + row * 128 + (((2 * bp + (mat >> 1)) ^ (lane & 7)) << 4);
            if (g < 2) stsm4(ad, pack_bf16(a0[4 * b], a0[4 * b + 1]), pack_bf16(a0[4 * b + 2], a0[4 * b + 3]), pack_bf16(a0[4 * b + 4], a0[4 * b + 5]), pack_bf16(a0[4 * b + 6], a0[4 * b + 7]));
            else stsm4(ad, pack_bf16(a1[4 * b], a1[4 * b + 1]), pack_bf16(a1[4 * b + 2], a1[4 * b + 3]), pack_bf16(a1[4 * b + 4], a1[4 * b + 5]), pack_bf16(a1[4 * b + 6], a1[4 * b + 7]));
        }
        fence_async_smem();
        bar_sync(1 + wg, 128);
        if (elect) { tma2d_store(&P.out, stg + g * 8192, br * 1024 + cb * 256 + g * 64, rb * 128 + wg * 64); bulk_commit(); }
    }
    if (elect) bulk_wait_all();
}

#define FMPOLY 0
__device__ __forceinline__ void feature_map(const float (&px)[16], uint32_t (&F)[8][2]) {
    const float L2E = 1.4426950408889634f;
    #pragma unroll
    for (int rr = 0; rr < 2; rr++) {
        float x[8];
        #pragma unroll
        for (int b = 0; b < 4; b++) {
            const uint32_t pk = pack_bf16(px[4 * b + 2 * rr], px[4 * b + 2 * rr + 1]);
            x[2 * b] = bf_lo(pk); x[2 * b + 1] = bf_hi(pk);
        }
        float mx = x[0], mn = x[0];
        #pragma unroll
        for (int i = 1; i < 8; i++) { mx = fmaxf(mx, x[i]); mn = fminf(mn, x[i]); }
        mx = fmaxf(mx, __shfl_xor_sync(0xffffffffu, mx, 1)); mn = fminf(mn, __shfl_xor_sync(0xffffffffu, mn, 1));
        mx = fmaxf(mx, __shfl_xor_sync(0xffffffffu, mx, 2)); mn = fminf(mn, __shfl_xor_sync(0xffffffffu, mn, 2));
        const float nmx = -mx * L2E, pmn = mn * L2E;
        float ep[8], en[8], sp = 0.f, sn = 0.f;
        #pragma unroll
        for (int i = 0; i < 8; i++) {
            const float ap = fmaf(x[i], L2E, nmx), an = fmaf(x[i], -L2E, pmn);
            ep[i] = ((FMPOLY >> i) & 1) ? exp2_fma(fmaxf(ap, -126.f)) : ex2(ap);
            en[i] = ((FMPOLY >> (8 + i)) & 1) ? exp2_fma(fmaxf(an, -126.f)) : ex2(an);
            sp += ep[i]; sn += en[i];
        }
        sp += __shfl_xor_sync(0xffffffffu, sp, 1); sn += __shfl_xor_sync(0xffffffffu, sn, 1);
        sp += __shfl_xor_sync(0xffffffffu, sp, 2); sn += __shfl_xor_sync(0xffffffffu, sn, 2);
        const float ip = __fdividef(1.f, sp), in = __fdividef(1.f, sn);
        #pragma unroll
        for (int b = 0; b < 4; b++) {
            F[b][rr] = pack_bf16(ep[2 * b] * ip, ep[2 * b + 1] * ip);
            F[4 + b][rr] = pack_bf16(en[2 * b] * in, en[2 * b + 1] * in);
        }
    }
}

__device__ __forceinline__ void a_epilogue(const float (&a)[96], uint32_t sb, int w4, int lane, int tile, int j, long long t0) {
    uint32_t fk[8][2];
    const int mat = lane >> 3, i = lane & 7;
    const uint32_t scr = sb + SCR_OFF;
    {
        #pragma unroll
        for (int hh = 0; hh < 2; hh++) {
            uint32_t vl[4], vh[4];
            pack32(a, 16 + hh * 4, 0, 1.f, vl);
            pack32(a, 16 + hh * 4, 1, 1.f, vh);
            #pragma unroll
            for (int bp = 0; bp < 2; bp++) {
                const int rowd = 8 * (2 * bp + (mat >> 1)) + i, chunk = 2 * w4 + (mat & 1);
                stsm4_t(scr + 16384 + hh * 5120 + rowd * 128 + ((chunk ^ i) << 4), vl[2 * bp], vh[2 * bp], vl[2 * bp + 1], vh[2 * bp + 1]);
            }
        }
        #pragma unroll
        for (int kk = 0; kk < 4; kk++)
            g_qfrag[(size_t)(tile * 4 + kk) * 128 + w4 * 32 + lane] = make_uint4(pack_bf16(a[8 * kk], a[8 * kk + 1]), pack_bf16(a[8 * kk + 2], a[8 * kk + 3]),
                                                                                  pack_bf16(a[8 * kk + 4], a[8 * kk + 5]), pack_bf16(a[8 * kk + 6], a[8 * kk + 7]));
        #pragma unroll
        for (int b = 0; b < 8; b++) {
            fk[b][0] = pack_bf16(a[4 * (8 + b)], a[4 * (8 + b) + 1]); fk[b][1] = pack_bf16(a[4 * (8 + b) + 2], a[4 * (8 + b) + 3]);
        }
    }
    ASTAMP(8);
    const uint64_t dw0 = D_K64 | desc_lo(sb + WPHI_OFF), dw1 = dw0 + 128;
    {
        float px0[16], px1[16];
        #pragma unroll
        for (int b = 0; b < 8; b++) fence_regs(fk[b]);
        wg_fence();
        wg_rs_n32(px0, fk[0][0], fk[0][1], fk[1][0], fk[1][1], dw0, 0);
        wg_rs_n32(px0, fk[2][0], fk[2][1], fk[3][0], fk[3][1], dw0 + 2, 1);
        wg_rs_n32(px1, fk[4][0], fk[4][1], fk[5][0], fk[5][1], dw1, 0);
        wg_rs_n32(px1, fk[6][0], fk[6][1], fk[7][0], fk[7][1], dw1 + 2, 1);
        wg_commit();
        wg_wait<0>();
        fence_regs(px0); fence_regs(px1);
        uint32_t F0[8][2], F1[8][2];
        feature_map(px0, F0);
        feature_map(px1, F1);
        #pragma unroll
        for (int bp = 0; bp < 4; bp++) {
            const int srow = w4 * 16 + (mat & 1) * 8 + i, chunk = 2 * bp + (mat >> 1);
            const uint32_t ad = scr + srow * 128 + ((chunk ^ i) << 4);
            stsm4(ad, F0[2 * bp][0], F0[2 * bp][1], F0[2 * bp + 1][0], F0[2 * bp + 1][1]);
            stsm4(ad + 8192, F1[2 * bp][0], F1[2 * bp][1], F1[2 * bp + 1][0], F1[2 * bp + 1][1]);
        }
    }
    ASTAMP(9);
    fence_async_smem();
    bar_sync(4, 128);
    float kv0[20], kv1[20];
    {
        const uint64_t dA0 = desc_hi(8192, 1024, 1) | desc_lo(scr), dA1 = dA0 + 512;
        const uint64_t dB0 = D_K128 | desc_lo(scr + 16384), dB1 = dB0 + 320;
        wg_fence();
        #pragma unroll
        for (int k = 0; k < 4; k++) wg_ss_n40_ta(kv0, dA0 + k * 128, dB0 + k * 2, k > 0 ? 1 : 0);
        #pragma unroll
        for (int k = 0; k < 4; k++) wg_ss_n40_ta(kv1, dA1 + k * 128, dB1 + k * 2, k > 0 ? 1 : 0);
        wg_commit();
        wg_wait<0>();
        fence_regs(kv0); fence_regs(kv1);
    }
    #pragma unroll
    for (int hh = 0; hh < 2; hh++) {
        float* dst = g_kv + (size_t)((2 * j + hh) * 64 + w4 * 16 + (lane >> 2)) * 40 + (lane & 3) * 2;
        #pragma unroll
        for (int b = 0; b < 5; b++) {
            if (b < 4 || (lane & 3) == 0) {
                #pragma unroll
                for (int rr = 0; rr < 2; rr++) {
                    const float v0 = hh == 0 ? kv0[4 * b + 2 * rr] : kv1[4 * b + 2 * rr], v1 = hh == 0 ? kv0[4 * b + 2 * rr + 1] : kv1[4 * b + 2 * rr + 1];
                    asm volatile("red.global.add.v2.f32 [%0], {%1, %2};" :: "l"(dst + rr * 8 * 40 + b * 8), "f"(v0), "f"(v1) : "memory");
                }
            }
        }
    }
    ASTAMP(10);
}

__device__ __forceinline__ void phi_q(const uint4 (&qf)[4], uint64_t dw0, uint64_t dw1, uint32_t (&F0)[8][2], uint32_t (&F1)[8][2]) {
    float px0[16], px1[16];
    uint32_t fq[16];
    #pragma unroll
    for (int q = 0; q < 4; q++) { fq[4 * q] = qf[q].x; fq[4 * q + 1] = qf[q].y; fq[4 * q + 2] = qf[q].z; fq[4 * q + 3] = qf[q].w; }
    fence_regs(fq);
    wg_fence();
    wg_rs_n32(px0, fq[0], fq[1], fq[2], fq[3], dw0, 0);
    wg_rs_n32(px0, fq[4], fq[5], fq[6], fq[7], dw0 + 2, 1);
    wg_rs_n32(px1, fq[8], fq[9], fq[10], fq[11], dw1, 0);
    wg_rs_n32(px1, fq[12], fq[13], fq[14], fq[15], dw1 + 2, 1);
    wg_commit();
    wg_wait<0>();
    fence_regs(px0); fence_regs(px1);
    feature_map(px0, F0);
    feature_map(px1, F1);
}

__device__ __forceinline__ void a_branch(uint32_t sb, uint8_t* sp, int w4, int lane, int r, int j, unsigned int epoch, const Params& P, long long t0) {
    const uint32_t bars = sb + BAR_OFF;
    const int tid = w4 * 32 + lane;
    const bool elect = (tid == 0);
    mbar_wait_long(bars + B_P1DONE * 8, 0);
    for (int i = tid; i < 2 * 256; i += 128) {
        const int hh = i >> 8, w = i & 255;
        *(uint32_t*)(sp + SCR_OFF + 16384 + hh * 5120 + 4096 + w * 4) = (w < 32) ? 0x3F803F80u : 0u;
    }
    #pragma unroll 1
    for (int i = 0; i < 4; i++) {
        float a[96];
        #pragma unroll
        for (int q = 0; q < 96; q++) a[q] = 0.f;
        fence_regs(a);
        const uint64_t da0 = D_K128 | desc_lo(sb + GX_OFF), db0 = desc_hi(4096, 1024, 1) | desc_lo(sb);
        #pragma unroll 1
        for (int ks = 0; ks < 32; ks += 8) {
            #pragma unroll
            for (int u = 0; u < 8; u++) {
                mbar_wait(bars + (B_GFULL + (u & 3)) * 8, (u >> 2) & 1);
                const uint64_t da = da0 + (((u >> 1) & 3) * GX_STAGE + (u & 1) * 64 >> 4), db = db0 + ((u & 3) * GW_STAGE >> 4);
                wg_fence();
                wg_ss_n192_tb(a, da, db, 1);
                wg_ss_n192_tb(a, da + 2, db + 128, 1);
                wg_commit();
                wg_wait<1>();
                mbar_arrive_if(bars + (B_GEMPTY + ((u + 3) & 3)) * 8, elect && (u > 0 || ks > 0));
            }
        }
        wg_wait<0>();
        mbar_arrive_if(bars + (B_GEMPTY + 3) * 8, elect);
        fence_regs(a);
        ASTAMP(2 * i);
        if (i == 0) { if (elect) flag_wait(&g_cntB[j], 8 * (epoch + 1)); }
        bar_sync(4, 128);
        a_epilogue(a, sb, w4, lane, (r * 4 + i) * 16 + j, j, t0);
        ASTAMP(2 * i + 1);
    }
    bar_sync(4, 128);
    if (elect) mbar_arrive(bars + B_KVDONE * 8);
    const uint64_t dw0 = D_K64 | desc_lo(sb + WPHI_OFF), dw1 = dw0 + 128;
    uint32_t F0[8][2], F1[8][2];
    uint4 qf[4];
    #pragma unroll
    for (int q = 0; q < 4; q++) qf[q] = __ldcg(&g_qfrag[(size_t)(((r * 4) * 16 + j) * 4 + q) * 128 + tid]);
    phi_q(qf, dw0, dw1, F0, F1);
    #pragma unroll
    for (int q = 0; q < 4; q++) qf[q] = __ldcg(&g_qfrag[(size_t)(((r * 4 + 1) * 16 + j) * 4 + q) * 128 + tid]);
    if (elect) flag_wait(&g_cntA[j], 8 * (epoch + 1));
    bar_sync(4, 128);
    STAMP(10);
    {
        const int hh = tid >> 6, fp = (tid >> 1) & 31, half = tid & 1, f = fp * 2;
        const float4* src0 = (const float4*)(g_kv + (size_t)((2 * j + hh) * 64 + f) * 40 + half * 20);
        float4 v0[5], v1[5];
        #pragma unroll
        for (int q = 0; q < 5; q++) { v0[q] = __ldcg(src0 + q); v1[q] = __ldcg(src0 + 10 + q); }
        #pragma unroll
        for (int q = 0; q < 5; q++) {
            const float e0[4] = {v0[q].x, v0[q].y, v0[q].z, v0[q].w}, e1[4] = {v1[q].x, v1[q].y, v1[q].z, v1[q].w};
            #pragma unroll
            for (int e = 0; e < 4; e++) {
                const int n = half * 20 + q * 4 + e;
                *(uint32_t*)(sp + SCR_OFF + hh * 5120 + n * 128 + (((f >> 3) ^ (n & 7)) << 4) + (f & 7) * 2) = n <= 32 ? pack_bf16(e0[e], e1[e]) : 0u;
            }
        }
    }
    fence_async_smem();
    bar_sync(4, 128);
    STAMP(8);
    {
        const uint64_t dB0 = D_K128 | desc_lo(sb + SCR_OFF), dB1 = dB0 + 320;
        #pragma unroll 1
        for (int i = 0; i < 4; i++) {
            float o0[20], o1[20];
            #pragma unroll
            for (int b = 0; b < 8; b++) { fence_regs(F0[b]); fence_regs(F1[b]); }
            wg_fence();
            #pragma unroll
            for (int kk = 0; kk < 4; kk++) wg_rs_n40(o0, F0[2 * kk][0], F0[2 * kk][1], F0[2 * kk + 1][0], F0[2 * kk + 1][1], dB0 + 2 * kk, kk > 0 ? 1 : 0);
            #pragma unroll
            for (int kk = 0; kk < 4; kk++) wg_rs_n40(o1, F1[2 * kk][0], F1[2 * kk][1], F1[2 * kk + 1][0], F1[2 * kk + 1][1], dB1 + 2 * kk, kk > 0 ? 1 : 0);
            wg_commit();
            wg_wait<0>();
            fence_regs(o0); fence_regs(o1);
            #pragma unroll
            for (int hh = 0; hh < 2; hh++) {
                uint32_t vl[4];
                #pragma unroll
                for (int rr = 0; rr < 2; rr++) {
                    float den = __shfl_sync(0xffffffffu, hh == 0 ? o0[16 + 2 * rr] : o1[16 + 2 * rr], lane & ~3);
                    den = bf_round(bf_round(den) + 1e-6f);
                    const float inv = 1.f / den;
                    uint32_t v[4];
                    #pragma unroll
                    for (int b = 0; b < 4; b++) {
                        const uint32_t pk = hh == 0 ? pack_bf16(o0[4 * b + 2 * rr], o0[4 * b + 2 * rr + 1]) : pack_bf16(o1[4 * b + 2 * rr], o1[4 * b + 2 * rr + 1]);
                        v[b] = pack_bf16(bf_lo(pk) * inv, bf_hi(pk) * inv);
                    }
                    if (rr == 0) { vl[0] = v[0]; vl[1] = v[1]; vl[2] = v[2]; vl[3] = v[3]; }
                    else {
                        const int srow = (i & 1) * 64 + w4 * 16 + ((lane >> 3) & 1) * 8 + (lane & 7);
                        #pragma unroll
                        for (int bp = 0; bp < 2; bp++)
                            stsm4(sb + (i >> 1) * 16384 + srow * 128 + (((hh * 4 + 2 * bp + (lane >> 4)) ^ (lane & 7)) << 4), vl[2 * bp], v[2 * bp], vl[2 * bp + 1], v[2 * bp + 1]);
                    }
                }
            }
            if (i == 3) break;
            phi_q(qf, dw0, dw1, F0, F1);
            const int in = i + 2 < 4 ? i + 2 : 3;
            #pragma unroll
            for (int q = 0; q < 4; q++) qf[q] = __ldcg(&g_qfrag[(size_t)(((r * 4 + in) * 16 + j) * 4 + q) * 128 + tid]);
        }
    }
    fence_async_smem();
    bar_sync(4, 128);
    if (elect) {
        for (int u = 0; u < 2; u++) tma2d_store(&P.o, sb + u * 16384, j * 64, r * 256 + u * 128);
        bulk_commit();
        bulk_wait_all();
        mbar_arrive(bars + B_ADONE * 8);
        asm volatile("fence.proxy.async.global;" ::: "memory");
        flag_signal_relaxed(&g_cntOA[r]);
    }
    STAMP(11);
}

__global__ void __launch_bounds__(512, 1) fused_kernel(const __grid_constant__ Params P) {
    extern __shared__ uint8_t smem_raw[];
    const uint32_t sb = (smem_u32(smem_raw) + 1023) & ~1023u;
    uint8_t* sp = smem_raw + (sb - smem_u32(smem_raw));
    const uint32_t bars = sb + BAR_OFF;
    const int c = blockIdx.x, r = c & 7, j = c >> 3;
    if (threadIdx.x == 384) {
        GT1(0);
        for (int s = 0; s < R1_N; s++) { mbar_init(bars + (B_FULL1 + s) * 8, 1); mbar_init(bars + (B_EMPTY1 + s) * 8, 2); }
        asm volatile("fence.mbarrier_init.release.cluster;" ::: "memory");
        fence_async_smem();
        for (int ks = 0; ks < R1_N; ks++) {
            const uint32_t st = sb + ks * R1_STAGE, fb = bars + (B_FULL1 + ks) * 8;
            mbar_expect_tx(fb, R1_STAGE);
            tma2d(st, &P.xB, ks * 64, r * 256, fb);
            tma3d(st + R1_A, &P.wB, j * 64, ks * 64, 0, fb);
        }
        GT1(1);
    }
    if (threadIdx.x < 120) {
        const int i = threadIdx.x;
        const char* src = i < 48 ? (const char*)P.pxB + (size_t)(r * 256 + j * 16 + i / 3) * 2048 + (i % 3) * 128
                                 : (const char*)P.pwB + (size_t)(r * 24 + (i - 48) / 3) * 6144 + ((i - 48) % 3) * 2048 + j * 128;
        asm volatile("prefetch.global.L2 [%0];" :: "l"(src));
    }
    const int warp = __shfl_sync(0xffffffffu, (int)(threadIdx.x >> 5), 0), lane = threadIdx.x & 31, wg = warp >> 2, w4 = warp & 3;
    const unsigned int epoch = __ldcg(&g_epoch[c]);
    if (threadIdx.x == 416) { prefetch_map(&P.xA); prefetch_map(&P.wA); prefetch_map(&P.o); prefetch_map(&P.oS); prefetch_map(&P.woA); prefetch_map(&P.woB); prefetch_map(&P.out); }
    if (threadIdx.x == 0) {
        for (int s = 0; s < KV_N; s++) { mbar_init(bars + (B_KVFULL + s) * 8, 1); mbar_init(bars + (B_KVEMPTY + s) * 8, 2); }
        for (int s = 0; s < G_N; s++) { mbar_init(bars + (B_GFULL + s) * 8, 1); mbar_init(bars + (B_GEMPTY + s) * 8, 1); }
        for (int q = 0; q < 6; q++) *((unsigned int*)(sp + NORM_OFF) + q) = 0u;
    }
    if (threadIdx.x == 32) {
        for (int s = 0; s < R3_N; s++) { mbar_init(bars + (B_FULL3 + s) * 8, 1); mbar_init(bars + (B_EMPTY3 + s) * 8, 2); }
        mbar_init(bars + B_R1FREE * 8, 1); mbar_init(bars + B_P1DONE * 8, 1); mbar_init(bars + B_P2DONE * 8, 2); mbar_init(bars + B_ADONE * 8, 1);
        mbar_init(bars + B_NORMOK * 8, 1); mbar_init(bars + B_ODONE * 8, 4); mbar_init(bars + (B_ODONE + 1) * 8, 4);
        mbar_init(bars + B_KVDONE * 8, 1); mbar_init(bars + B_KVSTAGED * 8, 1);
    }
    if (threadIdx.x == 0 || threadIdx.x == 32) asm volatile("fence.mbarrier_init.release.cluster;" ::: "memory");
    __syncthreads();
    if (threadIdx.x == 0) GT1(2);
    const long long t0 = 0;

    if (wg == 3) {
        reg_dealloc<24>();
        if (warp == 12) {
            for (int ks = R1_N; ks < 16; ks++) {
                const int s = ks % R1_N;
                mbar_wait(bars + (B_EMPTY1 + s) * 8, ((ks / R1_N) - 1) & 1);
                const uint32_t st = sb + s * R1_STAGE, fb = bars + (B_FULL1 + s) * 8;
                if (elect_one()) {
                    mbar_expect_tx(fb, R1_STAGE);
                    tma2d(st, &P.xB, ks * 64, r * 256, fb);
                    tma3d(st + R1_A, &P.wB, j * 64, ks * 64, 0, fb);
                    if (ks >= 3 && ks < 13) {
                        const int q = ks - 3;
                        const char* src = q < 6 ? (const char*)P.pwA + (size_t)c * 49152 + q * 8192 : (const char*)P.pxA + (size_t)c * 32768 + (q - 6) * 8192;
                        asm volatile("cp.async.bulk.prefetch.L2.global [%0], %1;" :: "l"(src), "r"(8192u) : "memory");
                    }
                }
                __syncwarp();
            }
            mbar_wait_long(bars + B_KVSTAGED * 8, 0);
            if (lane == 0) {
                for (int q = 0; q < 4; q++) {
                    const int hh = q >> 1, w = q & 1;
                    const uint32_t st = sb + KV_OFF + q * KV_STAGE;
                    bulk_store(&g_kimg[(size_t)((2 * j + hh) * 16 + 2 * r + w) * 512], st, 8192);
                    bulk_store(&g_vimg[(size_t)((2 * j + hh) * 32 + (2 * r + w) * 2) * 256], st + 8192, 4096);
                    bulk_store(&g_vimg[(size_t)((2 * j + hh) * 32 + (2 * r + w) * 2 + 1) * 256], st + 8192 + 5120, 4096);
                }
                bulk_commit();
                {
                    float chk = 0.f;
                    for (int q = 0; q < 4; q++) {
                        float* dst = &g_norm[((q >> 1) * NH + 2 * j + (q & 1)) * 8 + r];
                        asm volatile("st.relaxed.gpu.global.f32 [%0], %1;" :: "l"(dst), "f"(__uint_as_float(*((volatile unsigned int*)(sp + NORM_OFF) + 2 + q))) : "memory");
                        float v; asm volatile("ld.relaxed.gpu.global.f32 %0, [%1];" : "=f"(v) : "l"(dst) : "memory");
                        chk += v;
                    }
                    asm volatile("" :: "f"(chk) : "memory");
                }
                bulk_wait_all();
                asm volatile("fence.proxy.async.global;" ::: "memory");
                flag_signal_relaxed(&g_cntB[j]);
                flag_wait(&g_cntB[j], 8 * (epoch + 1));
                asm volatile("fence.proxy.async.global;" ::: "memory");
            }
            __syncwarp();
            for (int g = 2; g < 32; g++) {
                const int s = g & 3, h = 2 * j + (g >> 4), t = (2 * r + g) & 15;
                if (g >= KV_N) mbar_wait_long(bars + (B_KVEMPTY + s) * 8, ((g >> 2) - 1) & 1);
                const uint32_t st = sb + KV_OFF + s * KV_STAGE, fb = bars + (B_KVFULL + s) * 8;
                if (elect_one()) {
                    mbar_expect_tx(fb, 16384);
                    bulk_load(st, &g_kimg[(size_t)(h * 16 + t) * 512], 8192, fb);
                    bulk_load(st + 8192, &g_vimg[(size_t)(h * 32 + 2 * t) * 256], 4096, fb);
                    bulk_load(st + 8192 + 5120, &g_vimg[(size_t)(h * 32 + 2 * t + 1) * 256], 4096, fb);
                    if (g >= 8 && g < 12) {
                        const char* src = (g < 10 ? (const char*)P.pwoA : (const char*)P.pwoB) + (size_t)c * 16384 + (g & 1) * 8192;
                        asm volatile("cp.async.bulk.prefetch.L2.global [%0], %1;" :: "l"(src), "r"(8192u) : "memory");
                    }
                }
                __syncwarp();
                if (g == 3) {
                    mbar_wait(bars + B_P1DONE * 8, 0);
                    float v = __ldcg(&g_norm[((lane >> 4) * NH + 2 * j + ((lane >> 3) & 1)) * 8 + (lane & 7)]);
                    v = fmaxf(v, __shfl_xor_sync(0xffffffffu, v, 1)); v = fmaxf(v, __shfl_xor_sync(0xffffffffu, v, 2)); v = fmaxf(v, __shfl_xor_sync(0xffffffffu, v, 4));
                    const float nk0 = __shfl_sync(0xffffffffu, v, 0), nk1 = __shfl_sync(0xffffffffu, v, 8), nv0 = __shfl_sync(0xffffffffu, v, 16), nv1 = __shfl_sync(0xffffffffu, v, 24);
                    if (lane == 0) {
                        const volatile float* nloc = (const volatile float*)(sp + NORM_OFF);
                        *((volatile unsigned int*)(sp + NORM_OFF) + 8) = (scores_bounded(nloc[0], nk0, nv0) ? 1u : 0u) | (scores_bounded(nloc[1], nk1, nv1) ? 2u : 0u);
                        mbar_arrive(bars + B_NORMOK * 8);
                    }
                    __syncwarp();
                }
            }
            const int br = c >> 6, rb = c & 15, cb = (c >> 4) & 3;
            for (int ks = 0; ks < 16; ks++) {
                const int s = ks & 3;
                if (ks == 0) {
                    mbar_wait_long(bars + B_ADONE * 8, 0);
                    if (lane == 0) {
                        if (br == 0) flag_wait(&g_cntOA[rb >> 1], 16 * (epoch + 1)); else flag_wait(&g_cntOB[rb >> 1], 32 * (epoch + 1));
                        asm volatile("fence.proxy.async.global;" ::: "memory");
                    }
                    __syncwarp();
                }
                if (ks == 1) mbar_wait(bars + (B_KVEMPTY + 0) * 8, 1);
                if (ks == 2) { mbar_wait(bars + (B_KVEMPTY + 1) * 8, 1); mbar_wait(bars + (B_KVEMPTY + 2) * 8, 1); mbar_wait(bars + (B_KVEMPTY + 3) * 8, 1); }
                if (ks == 3) mbar_wait(bars + B_P2DONE * 8, 0);
                if (ks == 8 && br == 1) {
                    if (lane == 0) { flag_wait(&g_cntOB[8 + (rb >> 1)], 32 * (epoch + 1)); asm volatile("fence.proxy.async.global;" ::: "memory"); }
                    __syncwarp();
                }
                if (ks >= R3_N) mbar_wait(bars + (B_EMPTY3 + s) * 8, ((ks >> 2) - 1) & 1);
                const uint32_t st = sb + s * R3_STAGE, fb = bars + (B_FULL3 + s) * 8;
                if (elect_one()) {
                    mbar_expect_tx(fb, R3_STAGE);
                    tma2d(st, &P.o, ks * 64, br * SEQ + rb * 128, fb);
                    if (br == 0) tma3d(st + R3_A, &P.woA, 0, ks * 64, cb * 4, fb);
                    else tma5d(st + R3_A, &P.woB, 0, 0, ks >> 3, 2 * (ks & 7), cb * 4, fb);
                }
                __syncwarp();
            }
        } else if (warp == 13) {
            mbar_wait_long(bars + B_R1FREE * 8, 0);
            for (int it = 0; it < 128; it++) {
                const int s = it & 3, i = it >> 5, ks = it & 31;
                if (it >= G_N) mbar_wait(bars + (B_GEMPTY + s) * 8, ((it >> 2) - 1) & 1);
                const uint32_t fb = bars + (B_GFULL + s) * 8;
                if (elect_one()) {
                    mbar_expect_tx(fb, (it & 1) ? GW_STAGE : GW_STAGE + GX_STAGE);
                    if (!(it & 1)) tma2d(sb + GX_OFF + ((it >> 1) & 3) * GX_STAGE, &P.xA, ks * 32, r * 256 + i * 64, fb);
                    tma3d(sb + s * GW_STAGE, &P.wA, j * 64, ks * 32, 0, fb);
                }
                __syncwarp();
            }
        } else if (warp == 15) {
            if (lane == 0) {
                for (int q = 0; q < 4; q++) {
                    const int w = q & 1, task = q >> 1;
                    mbar_wait_long(bars + (B_ODONE + w) * 8, task);
                    tma2d_store(&P.oS, sb + Q_OFF + task * 16384 + w * 8192, task * 512 + j * 32, SEQ + r * 256 + w * 128);
                    bulk_commit();
                    bulk_wait_all();
                    if (task == 1) mbar_arrive(bars + B_P2DONE * 8);
                    asm volatile("fence.proxy.async.global;" ::: "memory");
                    flag_signal_relaxed(&g_cntOB[task * 8 + r]);
                }
            }
        } else {
            mbar_wait_long(bars + B_R1FREE * 8, 0);
            for (int i = lane; i < KV_N * 2 * 64; i += 32) {
                const int w = i & 63;
                *(uint4*)(sp + KV_OFF + (i >> 7) * KV_STAGE + 8192 + ((i >> 6) & 1) * 5120 + 4096 + w * 16) =
                    w < 8 ? make_uint4(0x3F803F80u, 0x3F803F80u, 0x3F803F80u, 0x3F803F80u) : make_uint4(0u, 0u, 0u, 0u);
            }
            fence_async_smem();
            __syncwarp();
            if (lane == 0) {
                mbar_wait(bars + B_KVSTAGED * 8, 0);
                mbar_arrive(bars + (B_KVFULL + 0) * 8);
                mbar_arrive(bars + (B_KVFULL + 1) * 8);
                mbar_wait_long(bars + B_KVDONE * 8, 0);
                flag_signal(&g_cntA[j]);
            }
        }
    } else if (wg == 2) {
        reg_dealloc<24>();
        for (int i = threadIdx.x & 127; i < 2048; i += 128) {
            const int hh = i >> 10, d = (i >> 5) & 31, f = i & 31;
            *(__nv_bfloat16*)(sp + WPHI_OFF + hh * 2048 + f * 64 + (((d >> 3) ^ ((f >> 1) & 3)) << 4) + (d & 7) * 2) = P.wphi[(size_t)(2 * j + hh) * 1024 + d * 32 + f];
        }
        fence_async_smem();
        mbar_wait_long(bars + B_P1DONE * 8, 0);
        reg_alloc<152>();
        a_branch(sb, sp, w4, lane, r, j, epoch, P, t0);
    } else {
        reg_alloc<232>();
        if (r == 0) {
            float4* z = (float4*)(g_kv + (size_t)2 * j * 64 * 40);
            for (int i = threadIdx.x; i < 2 * 64 * 40 / 4; i += 256) z[i] = make_float4(0.f, 0.f, 0.f, 0.f);
            __threadfence();
        }
        GSTAMP(0);
        phase1(sb, sp, wg, w4, lane, t0);
        GSTAMP(1);
        reg_dealloc<168>();
        attention(sb, sp, wg, w4, lane, t0);
        GSTAMP(2);
        phase3(sb, wg, w4, lane, c, P, t0);
        GSTAMP(3);
        if (threadIdx.x == 0) g_epoch[c] = epoch + 1;
    }
}

typedef CUresult (*EncodeFn)(CUtensorMap*, CUtensorMapDataType, cuuint32_t, void*, const cuuint64_t*, const cuuint64_t*, const cuuint32_t*,
                             const cuuint32_t*, CUtensorMapInterleave, CUtensorMapSwizzle, CUtensorMapL2promotion, CUtensorMapFloatOOBfill);
static void make_map(EncodeFn enc, CUtensorMap* m, const void* ptr, uint64_t inner, uint64_t outer, uint32_t box_inner, uint32_t box_outer, CUtensorMapSwizzle swz) {
    cuuint64_t gd[2] = {inner, outer}; cuuint64_t gs[1] = {inner * 2}; cuuint32_t bd[2] = {box_inner, box_outer}; cuuint32_t es[2] = {1, 1};
    enc(m, CU_TENSOR_MAP_DATA_TYPE_BFLOAT16, 2, const_cast<void*>(ptr), gd, gs, bd, es, CU_TENSOR_MAP_INTERLEAVE_NONE, swz,
        CU_TENSOR_MAP_L2_PROMOTION_L2_128B, CU_TENSOR_MAP_FLOAT_OOB_FILL_NONE);
}

struct Dims { uint64_t v[5]; };
static void make_map_nd(EncodeFn enc, CUtensorMap* m, const void* ptr, int rank, Dims dims, Dims strides, Dims box) {
    cuuint64_t gd[5], gs[5]; cuuint32_t bd[5], es[5];
    for (int i = 0; i < 5; i++) { gd[i] = dims.v[i]; gs[i] = strides.v[i]; bd[i] = (cuuint32_t)box.v[i]; es[i] = 1; }
    enc(m, CU_TENSOR_MAP_DATA_TYPE_BFLOAT16, rank, const_cast<void*>(ptr), gd, gs, bd, es, CU_TENSOR_MAP_INTERLEAVE_NONE, CU_TENSOR_MAP_SWIZZLE_128B,
        CU_TENSOR_MAP_L2_PROMOTION_L2_128B, CU_TENSOR_MAP_FLOAT_OOB_FILL_NONE);
}

}

extern "C" void kernel_launch(void* const* d_in, const int* in_sizes, int n_in, void* d_out, int out_size) {
    using namespace hk;
    (void)in_sizes; (void)n_in; (void)out_size;
    const __nv_bfloat16* A_x = (const __nv_bfloat16*)d_in[0];
    const __nv_bfloat16* A_wqkv = (const __nv_bfloat16*)d_in[1];
    const __nv_bfloat16* A_wphi = (const __nv_bfloat16*)d_in[2];
    const __nv_bfloat16* A_wo = (const __nv_bfloat16*)d_in[3];
    const __nv_bfloat16* B_x = (const __nv_bfloat16*)d_in[4];
    const __nv_bfloat16* B_wqkv = (const __nv_bfloat16*)d_in[5];
    const __nv_bfloat16* B_wo = (const __nv_bfloat16*)d_in[6];
    static EncodeFn enc = nullptr;
    static void* p_o = nullptr;
    if (!enc) {
        void* fn = nullptr; cudaDriverEntryPointQueryResult qr;
        cudaGetDriverEntryPoint("cuTensorMapEncodeTiled", &fn, cudaEnableDefault, &qr);
        enc = (EncodeFn)fn;
        cudaGetSymbolAddress(&p_o, g_o);
        cudaFuncSetAttribute(fused_kernel, cudaFuncAttributeMaxDynamicSharedMemorySize, SMEM_BYTES);
    }
    Params P;
    const CUtensorMapSwizzle S128 = CU_TENSOR_MAP_SWIZZLE_128B, S64 = CU_TENSOR_MAP_SWIZZLE_64B;
    make_map(enc, &P.xB, B_x, DM, SEQ, 64, 256, S128);
    make_map_nd(enc, &P.wB, B_wqkv, 3, {DM, DM, 3}, {3 * DM * 2, DM * 2}, {64, 64, 3});
    make_map(enc, &P.xA, A_x, DM, SEQ, 64, 64, S128);
    make_map_nd(enc, &P.wA, A_wqkv, 3, {DM, DM, 3}, {3 * DM * 2, DM * 2}, {64, 32, 3});

    make_map(enc, &P.o, p_o, DM, 2 * SEQ, 64, 128, S128);
    make_map(enc, &P.oS, p_o, DM, 2 * SEQ, 32, 128, S64);
    make_map_nd(enc, &P.woA, A_wo, 3, {64, DM, 16}, {DM * 2, 128}, {64, 64, 4});
    make_map_nd(enc, &P.woB, B_wo, 5, {64, 32, 2, 16, 16}, {DM * 2, 32 * DM * 2, 64 * DM * 2, 128}, {64, 32, 1, 2, 4});

    P.pxB = B_x; P.pwB = B_wqkv; P.pxA = A_x; P.pwA = A_wqkv; P.pwoA = A_wo; P.pwoB = B_wo; P.wphi = A_wphi;
    make_map(enc, &P.out, d_out, 2 * DM, SEQ, 64, 64, S128);
    fused_kernel<<<128, 512, SMEM_BYTES, cudaStreamPerThread>>>(P);
}
```

```cpp
#include <cuda_runtime.h>
#include <cuda_bf16.h>
#include <cuda.h>
#include <stdint.h>

namespace hk {

constexpr int SEQ = 2048, DM = 1024, NH = 32;

__device__ uint4 g_kimg[NH * 16 * 512];
__device__ uint4 g_vimg[NH * 32 * 256];
__device__ __nv_bfloat16 g_o[2 * SEQ * DM];
__device__ uint4 g_qfrag[512 * 4 * 128];
__device__ float g_kv[NH * 64 * 40];
__device__ float g_norm[2 * NH * 8];
__device__ unsigned int g_cntB[32], g_cntA[16], g_cntOA[8], g_cntOB[16];
__device__ unsigned int g_epoch[128];

struct Params {
    CUtensorMap xB, wB, xA, wA, o, oS, woA, woB, out;
    const __nv_bfloat16 *pxB, *pwB, *pxA, *pwA, *pwoA, *pwoB, *wphi;
};

constexpr int R1_A = 256 * 64 * 2, R1_B = 192 * 64 * 2, R1_STAGE = R1_A + R1_B, R1_N = 3;
constexpr int GW_STAGE = 12288, G_N = 4, GX_OFF = G_N * GW_STAGE, GX_STAGE = 8192;
constexpr int KV_OFF = GX_OFF + 4 * GX_STAGE, KV_STAGE = 18432, KV_N = 4;
constexpr int Q_OFF = KV_OFF + KV_N * KV_STAGE;
constexpr int SCR_OFF = Q_OFF + 32768;
constexpr int WPHI_OFF = SCR_OFF + 26624;
constexpr int BAR_OFF = WPHI_OFF + 4096;
constexpr int R3_A = 128 * 64 * 2, R3_STAGE = R3_A + 256 * 64 * 2, R3_N = 4;
constexpr int SMEM_BYTES = BAR_OFF + 1024 + 1024;
static_assert(R3_N * R3_STAGE <= WPHI_OFF, "ring3");
static_assert(SMEM_BYTES <= 232448, "smem");
constexpr int B_FULL1 = 0, B_EMPTY1 = 3, B_KVFULL = 6, B_KVEMPTY = 10, B_GFULL = 16, B_GEMPTY = 21, B_FULL3 = 26, B_EMPTY3 = 30,
              B_R1FREE = 34, B_P1DONE = 35, B_P2DONE = 36, B_NORMOK = 37, B_ODONE = 38, B_KVDONE = 40, B_ADONE = 41, B_KVSTAGED = 42;
constexpr int NORM_OFF = BAR_OFF + 512;

__device__ __forceinline__ uint32_t smem_u32(const void* p) { return (uint32_t)__cvta_generic_to_shared(p); }
__device__ __forceinline__ void mbar_init(uint32_t bar, uint32_t cnt) { asm volatile("mbarrier.init.shared::cta.b64 [%0], %1;" :: "r"(bar), "r"(cnt) : "memory"); }
__device__ __forceinline__ void mbar_expect_tx(uint32_t bar, uint32_t bytes) { asm volatile("mbarrier.arrive.expect_tx.shared::cta.b64 _, [%0], %1;" :: "r"(bar), "r"(bytes) : "memory"); }
__device__ __forceinline__ void mbar_arrive(uint32_t bar) { asm volatile("mbarrier.arrive.shared::cta.b64 _, [%0];" :: "r"(bar) : "memory"); }
__device__ __forceinline__ void mbar_arrive_if(uint32_t bar, bool pred) {
    asm volatile("{\n.reg .pred p;\nsetp.ne.u32 p, %1, 0;\n@p mbarrier.arrive.shared::cta.b64 _, [%0];\n}\n" :: "r"(bar), "r"((uint32_t)pred) : "memory");
}
__device__ __forceinline__ void mbar_wait(uint32_t bar, uint32_t parity) {
    asm volatile("{\n.reg .pred p;\n.reg .u32 c;\nmov.u32 c, 0;\nLAB_WAIT:\nmbarrier.try_wait.parity.shared::cta.b64 p, [%0], %1;\n@p bra LAB_DONE;\n"
                 "add.u32 c, c, 1;\nsetp.lt.u32 p, c, 4194304;\n@p bra LAB_WAIT;\ntrap;\nLAB_DONE:\n}\n" :: "r"(bar), "r"(parity) : "memory");
}
__device__ __forceinline__ void mbar_wait_long(uint32_t bar, uint32_t parity) {
    asm volatile("{\n.reg .pred p;\n.reg .u32 c;\nmov.u32 c, 0;\nLAB_WAIT:\nmbarrier.try_wait.parity.shared::cta.b64 p, [%0], %1, 100000;\n@p bra LAB_DONE;\n"
                 "add.u32 c, c, 1;\nsetp.lt.u32 p, c, 262144;\n@p bra LAB_WAIT;\ntrap;\nLAB_DONE:\n}\n" :: "r"(bar), "r"(parity) : "memory");
}
__device__ __forceinline__ void flag_wait(const unsigned int* cnt, unsigned int target) {
    asm volatile("{\n.reg .pred p;\n.reg .u32 c, v;\nmov.u32 c, 0;\nLAB_WAIT:\nld.acquire.gpu.global.u32 v, [%0];\nsub.u32 v, v, %1;\nsetp.ge.s32 p, v, 0;\n@p bra LAB_DONE;\n"
                 "nanosleep.u32 64;\nadd.u32 c, c, 1;\nsetp.lt.u32 p, c, 4194304;\n@p bra LAB_WAIT;\ntrap;\nLAB_DONE:\n}\n" :: "l"(cnt), "r"(target) : "memory");
}
__device__ __forceinline__ void flag_signal(unsigned int* cnt) {
    asm volatile("red.release.gpu.global.add.u32 [%0], 1;" :: "l"(cnt) : "memory");
}
__device__ __forceinline__ void flag_signal_relaxed(unsigned int* cnt) {
    asm volatile("red.relaxed.gpu.global.add.u32 [%0], 1;" :: "l"(cnt) : "memory");
}
__device__ __forceinline__ void tma2d(uint32_t dst, const CUtensorMap* m, int c0, int c1, uint32_t bar) {
    asm volatile("cp.async.bulk.tensor.2d.shared::cluster.global.mbarrier::complete_tx::bytes [%0], [%1, {%3, %4}], [%2];"
                 :: "r"(dst), "l"(m), "r"(bar), "r"(c0), "r"(c1) : "memory");
}
__device__ __forceinline__ void tma3d(uint32_t dst, const CUtensorMap* m, int c0, int c1, int c2, uint32_t bar) {
    asm volatile("cp.async.bulk.tensor.3d.shared::cluster.global.mbarrier::complete_tx::bytes [%0], [%1, {%3, %4, %5}], [%2];"
                 :: "r"(dst), "l"(m), "r"(bar), "r"(c0), "r"(c1), "r"(c2) : "memory");
}
__device__ __forceinline__ void tma5d(uint32_t dst, const CUtensorMap* m, int c0, int c1, int c2, int c3, int c4, uint32_t bar) {
    asm volatile("cp.async.bulk.tensor.5d.shared::cluster.global.mbarrier::complete_tx::bytes [%0], [%1, {%3, %4, %5, %6, %7}], [%2];"
                 :: "r"(dst), "l"(m), "r"(bar), "r"(c0), "r"(c1), "r"(c2), "r"(c3), "r"(c4) : "memory");
}
__device__ __forceinline__ bool elect_one() {
    uint32_t p;
    asm volatile("{\n.reg .pred P;\nelect.sync _|P, 0xffffffff;\nselp.u32 %0, 1, 0, P;\n}\n" : "=r"(p));
    return p != 0;
}
__device__ __forceinline__ void prefetch_map(const CUtensorMap* m) { asm volatile("prefetch.tensormap [%0];" :: "l"(m) : "memory"); }
__device__ __forceinline__ void tma2d_store(const CUtensorMap* m, uint32_t src, int c0, int c1) {
    asm volatile("cp.async.bulk.tensor.2d.global.shared::cta.bulk_group [%0, {%2, %3}], [%1];" :: "l"(m), "r"(src), "r"(c0), "r"(c1) : "memory");
}
__device__ __forceinline__ void bulk_load(uint32_t dst, const void* src, uint32_t bytes, uint32_t bar) {
    asm volatile("cp.async.bulk.shared::cluster.global.mbarrier::complete_tx::bytes [%0], [%1], %2, [%3];" :: "r"(dst), "l"(src), "r"(bytes), "r"(bar) : "memory");
}
__device__ __forceinline__ void bulk_store(void* dst, uint32_t src, uint32_t bytes) {
    asm volatile("cp.async.bulk.global.shared::cta.bulk_group [%0], [%1], %2;" :: "l"(dst), "r"(src), "r"(bytes) : "memory");
}
__device__ __forceinline__ void bulk_commit() { asm volatile("cp.async.bulk.commit_group;" ::: "memory"); }
__device__ __forceinline__ void bulk_wait_all() { asm volatile("cp.async.bulk.wait_group 0;" ::: "memory"); }
__device__ __forceinline__ void fence_async_smem() { asm volatile("fence.proxy.async.shared::cta;" ::: "memory"); }
__device__ __forceinline__ void fence_async_all() { asm volatile("fence.proxy.async;" ::: "memory"); }
__device__ __forceinline__ void wg_fence() { asm volatile("wgmma.fence.sync.aligned;" ::: "memory"); }
__device__ __forceinline__ void wg_commit() { asm volatile("wgmma.commit_group.sync.aligned;" ::: "memory"); }
template <int N> __device__ __forceinline__ void wg_wait() { asm volatile("wgmma.wait_group.sync.aligned %0;" :: "n"(N) : "memory"); }
__device__ __forceinline__ void bar_sync(int id, int n) { asm volatile("bar.sync %0, %1;" :: "r"(id), "r"(n) : "memory"); }
template <int N> __device__ __forceinline__ void reg_alloc() { asm volatile("setmaxnreg.inc.sync.aligned.u32 %0;" :: "n"(N)); }
template <int N> __device__ __forceinline__ void reg_dealloc() { asm volatile("setmaxnreg.dec.sync.aligned.u32 %0;" :: "n"(N)); }
__device__ __forceinline__ void stsm4(uint32_t addr, uint32_t r0, uint32_t r1, uint32_t r2, uint32_t r3) {
    asm volatile("stmatrix.sync.aligned.m8n8.x4.shared.b16 [%0], {%1, %2, %3, %4};" :: "r"(addr), "r"(r0), "r"(r1), "r"(r2), "r"(r3) : "memory");
}
__device__ __forceinline__ void stsm4_t(uint32_t addr, uint32_t r0, uint32_t r1, uint32_t r2, uint32_t r3) {
    asm volatile("stmatrix.sync.aligned.m8n8.x4.trans.shared.b16 [%0], {%1, %2, %3, %4};" :: "r"(addr), "r"(r0), "r"(r1), "r"(r2), "r"(r3) : "memory");
}
__host__ __device__ constexpr uint64_t desc_hi(uint32_t lbo, uint32_t sbo, int swz) {
    return ((uint64_t)((lbo & 0x3FFFF) >> 4) << 16) | ((uint64_t)((sbo & 0x3FFFF) >> 4) << 32) | ((uint64_t)swz << 62);
}
__device__ __forceinline__ uint64_t desc_lo(uint32_t addr) { return (uint64_t)((addr & 0x3FFFF) >> 4); }
constexpr uint64_t D_K128 = desc_hi(16, 1024, 1);
constexpr uint64_t D_K64 = desc_hi(16, 512, 2);
__device__ __forceinline__ uint32_t pack_bf16(float lo, float hi) {
    uint32_t r; asm("cvt.rn.bf16x2.f32 %0, %1, %2;" : "=r"(r) : "f"(hi), "f"(lo)); return r;
}
__device__ __forceinline__ float bf_lo(uint32_t r) { return __uint_as_float(r << 16); }
__device__ __forceinline__ float bf_hi(uint32_t r) { return __uint_as_float(r & 0xFFFF0000u); }
__device__ __forceinline__ float bf_round(float x) { return __bfloat162float(__float2bfloat16_rn(x)); }
__device__ __forceinline__ float ex2(float x) { float y; asm("ex2.approx.ftz.f32 %0, %1;" : "=f"(y) : "f"(x)); return y; }
template <int R> __device__ __forceinline__ void fence_regs(float (&d)[R]) {
    #pragma unroll
    for (int i = 0; i < R; i++) asm volatile("" : "+f"(d[i]) :: "memory");
}
template <int R> __device__ __forceinline__ void fence_regs(uint32_t (&d)[R]) {
    #pragma unroll
    for (int i = 0; i < R; i++) asm volatile("" : "+r"(d[i]) :: "memory");
}
__device__ __forceinline__ void quad_transpose(uint32_t (&r)[4], int t) {
    uint32_t s0 = (t & 1) ? r[0] : r[1], s1 = (t & 1) ? r[2] : r[3];
    s0 = __shfl_xor_sync(0xffffffffu, s0, 1); s1 = __shfl_xor_sync(0xffffffffu, s1, 1);
    if (t & 1) { r[0] = s0; r[2] = s1; } else { r[1] = s0; r[3] = s1; }
    s0 = (t & 2) ? r[0] : r[2]; s1 = (t & 2) ? r[1] : r[3];
    s0 = __shfl_xor_sync(0xffffffffu, s0, 2); s1 = __shfl_xor_sync(0xffffffffu, s1, 2);
    if (t & 2) { r[0] = s0; r[1] = s1; } else { r[2] = s0; r[3] = s1; }
}
template <int R> __device__ __forceinline__ void pack32(const float (&a)[R], int b0, int rr, float scale, uint32_t (&r)[4]) {
    #pragma unroll
    for (int b = 0; b < 4; b++) r[b] = pack_bf16(a[4 * (b0 + b) + 2 * rr] * scale, a[4 * (b0 + b) + 2 * rr + 1] * scale);
}
__device__ __forceinline__ float sumsq4(const uint32_t (&r)[4]) {
    float s = 0.f;
    #pragma unroll
    for (int b = 0; b < 4; b++) { float lo = bf_lo(r[b]), hi = bf_hi(r[b]); s = fmaf(lo, lo, s); s = fmaf(hi, hi, s); }
    s += __shfl_xor_sync(0xffffffffu, s, 1); s += __shfl_xor_sync(0xffffffffu, s, 2);
    return s;
}

__device__ __forceinline__ void wg_ss_n192_tb(float (&d)[96], uint64_t da, uint64_t db, int sd) {
    asm volatile("{\n.reg .pred p;\nsetp.ne.b32 p, %98, 0;\n"
        "wgmma.mma_async.sync.aligned.m64n192k16.f32.bf16.bf16 {"
        "%0, %1, %2, %3, %4, %5, %6, %7, %8, %9, %10, %11, %12, %13, %14, %15, "
        "%16, %17, %18, %19, %20, %21, %22, %23, %24, %25, %26, %27, %28, %29, %30, %31, "
        "%32, %33, %34, %35, %36, %37, %38, %39, %40, %41, %42, %43, %44, %45, %46, %47, "
        "%48, %49, %50, %51, %52, %53, %54, %55, %56, %57, %58, %59, %60, %61, %62, %63, "
        "%64, %65, %66, %67, %68, %69, %70, %71, %72, %73, %74, %75, %76, %77, %78, %79, "
        "%80, %81, %82, %83, %84, %85, %86, %87, %88, %89, %90, %91, %92, %93, %94, %95}, %96, %97, p, 1, 1, 0, 1;\n}\n"
        : "+f"(d[0]), "+f"(d[1]), "+f"(d[2]), "+f"(d[3]), "+f"(d[4]), "+f"(d[5]), "+f"(d[6]), "+f"(d[7]),
          "+f"(d[8]), "+f"(d[9]), "+f"(d[10]), "+f"(d[11]), "+f"(d[12]), "+f"(d[13]), "+f"(d[14]), "+f"(d[15]),
          "+f"(d[16]), "+f"(d[17]), "+f"(d[18]), "+f"(d[19]), "+f"(d[20]), "+f"(d[21]), "+f"(d[22]), "+f"(d[23]),
          "+f"(d[24]), "+f"(d[25]), "+f"(d[26]), "+f"(d[27]), "+f"(d[28]), "+f"(d[29]), "+f"(d[30]), "+f"(d[31]),
          "+f"(d[32]), "+f"(d[33]), "+f"(d[34]), "+f"(d[35]), "+f"(d[36]), "+f"(d[37]), "+f"(d[38]), "+f"(d[39]),
          "+f"(d[40]), "+f"(d[41]), "+f"(d[42]), "+f"(d[43]), "+f"(d[44]), "+f"(d[45]), "+f"(d[46]), "+f"(d[47]),
          "+f"(d[48]), "+f"(d[49]), "+f"(d[50]), "+f"(d[51]), "+f"(d[52]), "+f"(d[53]), "+f"(d[54]), "+f"(d[55]),
          "+f"(d[56]), "+f"(d[57]), "+f"(d[58]), "+f"(d[59]), "+f"(d[60]), "+f"(d[61]), "+f"(d[62]), "+f"(d[63]),
          "+f"(d[64]), "+f"(d[65]), "+f"(d[66]), "+f"(d[67]), "+f"(d[68]), "+f"(d[69]), "+f"(d[70]), "+f"(d[71]),
          "+f"(d[72]), "+f"(d[73]), "+f"(d[74]), "+f"(d[75]), "+f"(d[76]), "+f"(d[77]), "+f"(d[78]), "+f"(d[79]),
          "+f"(d[80]), "+f"(d[81]), "+f"(d[82]), "+f"(d[83]), "+f"(d[84]), "+f"(d[85]), "+f"(d[86]), "+f"(d[87]),
          "+f"(d[88]), "+f"(d[89]), "+f"(d[90]), "+f"(d[91]), "+f"(d[92]), "+f"(d[93]), "+f"(d[94]), "+f"(d[95])
        : "l"(da), "l"(db), "r"(sd));
}
__device__ __forceinline__ void wg_ss_n128_tb(float (&d)[64], uint64_t da, uint64_t db, int sd) {
    asm volatile("{\n.reg .pred p;\nsetp.ne.b32 p, %66, 0;\n"
        "wgmma.mma_async.sync.aligned.m64n128k16.f32.bf16.bf16 {"
        "%0, %1, %2, %3, %4, %5, %6, %7, %8, %9, %10, %11, %12, %13, %14, %15, "
        "%16, %17, %18, %19, %20, %21, %22, %23, %24, %25, %26, %27, %28, %29, %30, %31, "
        "%32, %33, %34, %35, %36, %37, %38, %39, %40, %41, %42, %43, %44, %45, %46, %47, "
        "%48, %49, %50, %51, %52, %53, %54, %55, %56, %57, %58, %59, %60, %61, %62, %63}, %64, %65, p, 1, 1, 0, 1;\n}\n"
        : "+f"(d[0]), "+f"(d[1]), "+f"(d[2]), "+f"(d[3]), "+f"(d[4]), "+f"(d[5]), "+f"(d[6]), "+f"(d[7]),
          "+f"(d[8]), "+f"(d[9]), "+f"(d[10]), "+f"(d[11]), "+f"(d[12]), "+f"(d[13]), "+f"(d[14]), "+f"(d[15]),
          "+f"(d[16]), "+f"(d[17]), "+f"(d[18]), "+f"(d[19]), "+f"(d[20]), "+f"(d[21]), "+f"(d[22]), "+f"(d[23]),
          "+f"(d[24]), "+f"(d[25]), "+f"(d[26]), "+f"(d[27]), "+f"(d[28]), "+f"(d[29]), "+f"(d[30]), "+f"(d[31]),
          "+f"(d[32]), "+f"(d[33]), "+f"(d[34]), "+f"(d[35]), "+f"(d[36]), "+f"(d[37]), "+f"(d[38]), "+f"(d[39]),
          "+f"(d[40]), "+f"(d[41]), "+f"(d[42]), "+f"(d[43]), "+f"(d[44]), "+f"(d[45]), "+f"(d[46]), "+f"(d[47]),
          "+f"(d[48]), "+f"(d[49]), "+f"(d[50]), "+f"(d[51]), "+f"(d[52]), "+f"(d[53]), "+f"(d[54]), "+f"(d[55]),
          "+f"(d[56]), "+f"(d[57]), "+f"(d[58]), "+f"(d[59]), "+f"(d[60]), "+f"(d[61]), "+f"(d[62]), "+f"(d[63])
        : "l"(da), "l"(db), "r"(sd));
}
__device__ __forceinline__ void wg_ss_n64(float (&d)[32], uint64_t da, uint64_t db, int sd) {
    asm volatile("{\n.reg .pred p;\nsetp.ne.b32 p, %34, 0;\n"
        "wgmma.mma_async.sync.aligned.m64n64k16.f32.bf16.bf16 {"
        "%0, %1, %2, %3, %4, %5, %6, %7, %8, %9, %10, %11, %12, %13, %14, %15, "
        "%16, %17, %18, %19, %20, %21, %22, %23, %24, %25, %26, %27, %28, %29, %30, %31}, %32, %33, p, 1, 1, 0, 0;\n}\n"
        : "+f"(d[0]), "+f"(d[1]), "+f"(d[2]), "+f"(d[3]), "+f"(d[4]), "+f"(d[5]), "+f"(d[6]), "+f"(d[7]),
          "+f"(d[8]), "+f"(d[9]), "+f"(d[10]), "+f"(d[11]), "+f"(d[12]), "+f"(d[13]), "+f"(d[14]), "+f"(d[15]),
          "+f"(d[16]), "+f"(d[17]), "+f"(d[18]), "+f"(d[19]), "+f"(d[20]), "+f"(d[21]), "+f"(d[22]), "+f"(d[23]),
          "+f"(d[24]), "+f"(d[25]), "+f"(d[26]), "+f"(d[27]), "+f"(d[28]), "+f"(d[29]), "+f"(d[30]), "+f"(d[31])
        : "l"(da), "l"(db), "r"(sd));
}
__device__ __forceinline__ void wg_rs_n40(float (&d)[20], uint32_t a0, uint32_t a1, uint32_t a2, uint32_t a3, uint64_t db, int sd) {
    asm volatile("{\n.reg .pred p;\nsetp.ne.b32 p, %25, 0;\n"
        "wgmma.mma_async.sync.aligned.m64n40k16.f32.bf16.bf16 {"
        "%0, %1, %2, %3, %4, %5, %6, %7, %8, %9, %10, %11, %12, %13, %14, %15, "
        "%16, %17, %18, %19}, {%20, %21, %22, %23}, %24, p, 1, 1, 0;\n}\n"
        : "+f"(d[0]), "+f"(d[1]), "+f"(d[2]), "+f"(d[3]), "+f"(d[4]), "+f"(d[5]), "+f"(d[6]), "+f"(d[7]),
          "+f"(d[8]), "+f"(d[9]), "+f"(d[10]), "+f"(d[11]), "+f"(d[12]), "+f"(d[13]), "+f"(d[14]), "+f"(d[15]),
          "+f"(d[16]), "+f"(d[17]), "+f"(d[18]), "+f"(d[19])
        : "r"(a0), "r"(a1), "r"(a2), "r"(a3), "l"(db), "r"(sd));
}
__device__ __forceinline__ void wg_rs_n32(float (&d)[16], uint32_t a0, uint32_t a1, uint32_t a2, uint32_t a3, uint64_t db, int sd) {
    asm volatile("{\n.reg .pred p;\nsetp.ne.b32 p, %21, 0;\n"
        "wgmma.mma_async.sync.aligned.m64n32k16.f32.bf16.bf16 {"
        "%0, %1, %2, %3, %4, %5, %6, %7, %8, %9, %10, %11, %12, %13, %14, %15}, {%16, %17, %18, %19}, %20, p, 1, 1, 0;\n}\n"
        : "+f"(d[0]), "+f"(d[1]), "+f"(d[2]), "+f"(d[3]), "+f"(d[4]), "+f"(d[5]), "+f"(d[6]), "+f"(d[7]),
          "+f"(d[8]), "+f"(d[9]), "+f"(d[10]), "+f"(d[11]), "+f"(d[12]), "+f"(d[13]), "+f"(d[14]), "+f"(d[15])
        : "r"(a0), "r"(a1), "r"(a2), "r"(a3), "l"(db), "r"(sd));
}
__device__ __forceinline__ void wg_ss_n40_ta(float (&d)[20], uint64_t da, uint64_t db, int sd) {
    asm volatile("{\n.reg .pred p;\nsetp.ne.b32 p, %22, 0;\n"
        "wgmma.mma_async.sync.aligned.m64n40k16.f32.bf16.bf16 {"
        "%0, %1, %2, %3, %4, %5, %6, %7, %8, %9, %10, %11, %12, %13, %14, %15, "
        "%16, %17, %18, %19}, %20, %21, p, 1, 1, 1, 0;\n}\n"
        : "+f"(d[0]), "+f"(d[1]), "+f"(d[2]), "+f"(d[3]), "+f"(d[4]), "+f"(d[5]), "+f"(d[6]), "+f"(d[7]),
          "+f"(d[8]), "+f"(d[9]), "+f"(d[10]), "+f"(d[11]), "+f"(d[12]), "+f"(d[13]), "+f"(d[14]), "+f"(d[15]),
          "+f"(d[16]), "+f"(d[17]), "+f"(d[18]), "+f"(d[19])
        : "l"(da), "l"(db), "r"(sd));
}

__device__ __forceinline__ float acc_sumsq(const float (&a)[96], int b0, int rr) {
    float s = 0.f;
    #pragma unroll
    for (int b = 0; b < 4; b++) { s = fmaf(a[4 * (b0 + b) + 2 * rr], a[4 * (b0 + b) + 2 * rr], s); s = fmaf(a[4 * (b0 + b) + 2 * rr + 1], a[4 * (b0 + b) + 2 * rr + 1], s); }
    return s;
}
__device__ __forceinline__ float quad_norms(const float (&a)[96], int X, int t) {
    const float p0 = acc_sumsq(a, X * 8, 0), p1 = acc_sumsq(a, X * 8, 1), p2 = acc_sumsq(a, X * 8 + 4, 0), p3 = acc_sumsq(a, X * 8 + 4, 1);
    const float k0 = (t & 1) ? p1 : p0, s0 = (t & 1) ? p0 : p1, k1 = (t & 1) ? p3 : p2, s1 = (t & 1) ? p2 : p3;
    const float u0 = k0 + __shfl_xor_sync(0xffffffffu, s0, 1), u1 = k1 + __shfl_xor_sync(0xffffffffu, s1, 1);
    return ((t & 2) ? u1 : u0) + __shfl_xor_sync(0xffffffffu, (t & 2) ? u0 : u1, 2);
}
__device__ __forceinline__ void publish_norm(float v, int X, uint8_t* sp, int lane) {
    v = fmaxf(v, __shfl_xor_sync(0xffffffffu, v, 1));
    v = fmaxf(v, __shfl_xor_sync(0xffffffffu, v, 4)); v = fmaxf(v, __shfl_xor_sync(0xffffffffu, v, 8)); v = fmaxf(v, __shfl_xor_sync(0xffffffffu, v, 16));
    if ((lane & ~2) == 0) atomicMax((unsigned int*)(sp + NORM_OFF) + X * 2 + (lane >> 1), __float_as_uint(v * (X == 0 ? 1.02f * 0.0650428f : 1.02f)));
}
template <int X>
__device__ __forceinline__ void p1_store_rows(const float (&a)[96], int m, int wg, int w4, int lane, uint32_t sb) {
    const float QS = 0.17677669529663687f * 1.4426950408889634f;
    const int mat = lane >> 3, i = lane & 7;
    #pragma unroll
    for (int hh = 0; hh < 2; hh++) {
        uint32_t vl[4], vh[4];
        pack32(a, X * 8 + hh * 4, 0, X == 0 ? QS : 1.f, vl);
        pack32(a, X * 8 + hh * 4, 1, X == 0 ? QS : 1.f, vh);
        const int row = m * 64 + w4 * 16 + (mat & 1) * 8 + i;
        const uint32_t base = (X == 0 ? sb + Q_OFF + hh * 16384 + wg * 8192 : sb + KV_OFF + (hh * 2 + wg) * KV_STAGE) + row * 64;
        #pragma unroll
        for (int bp = 0; bp < 2; bp++)
            stsm4(base + (((2 * bp + (mat >> 1)) ^ ((row >> 1) & 3)) << 4), vl[2 * bp], vh[2 * bp], vl[2 * bp + 1], vh[2 * bp + 1]);
    }
}
__device__ __forceinline__ void p1_store_vt(const float (&a)[96], int m, int wg, int w4, int lane, uint32_t sb) {
    const int mat = lane >> 3, i = lane & 7;
    #pragma unroll
    for (int hh = 0; hh < 2; hh++) {
        uint32_t vl[4], vh[4];
        pack32(a, 16 + hh * 4, 0, 1.f, vl);
        pack32(a, 16 + hh * 4, 1, 1.f, vh);
        const uint32_t base = sb + KV_OFF + (hh * 2 + wg) * KV_STAGE + 8192 + m * 5120;
        #pragma unroll
        for (int bp = 0; bp < 2; bp++) {
            const int rowd = 8 * (2 * bp + (mat >> 1)) + i, chunk = 2 * w4 + (mat & 1);
            stsm4_t(base + rowd * 128 + ((chunk ^ i) << 4), vl[2 * bp], vh[2 * bp], vl[2 * bp + 1], vh[2 * bp + 1]);
        }
    }
}

__device__ __forceinline__ void phase1(uint32_t sb, uint8_t* sp, int wg, int w4, int lane) {
    const uint32_t bars = sb + BAR_OFF;
    const bool elect = (w4 == 0 && lane == 0);
    float a0[96], a1[96];
    #pragma unroll 1
    for (int ks = 0; ks < 16; ks++) {
        const int s = ks % R1_N;
        mbar_wait(bars + (B_FULL1 + s) * 8, (ks / R1_N) & 1);
        const uint32_t st = sb + s * R1_STAGE;
        const uint64_t da = D_K128 | desc_lo(st + wg * 16384);
        const uint64_t db = desc_hi(8192, 1024, 1) | desc_lo(st + R1_A);
        wg_fence();
        #pragma unroll
        for (int k = 0; k < 4; k++) {
            wg_ss_n192_tb(a0, da + k * 2, db + k * 128, (ks > 0 || k > 0) ? 1 : 0);
            wg_ss_n192_tb(a1, da + 512 + k * 2, db + k * 128, (ks > 0 || k > 0) ? 1 : 0);
        }
        wg_commit();
        wg_wait<0>();
        mbar_arrive_if(bars + (B_EMPTY1 + s) * 8, elect);
    }
    fence_regs(a0); fence_regs(a1);
    bar_sync(3, 256);
    const int tid = wg * 128 + w4 * 32 + lane;
    if (tid == 0) mbar_arrive(bars + B_R1FREE * 8);
    const int t = lane & 3;
    p1_store_rows<1>(a0, 0, wg, w4, lane, sb); p1_store_vt(a0, 0, wg, w4, lane, sb);
    p1_store_rows<1>(a1, 1, wg, w4, lane, sb); p1_store_vt(a1, 1, wg, w4, lane, sb);
    fence_async_smem();
    publish_norm(fmaxf(quad_norms(a0, 1, t), quad_norms(a1, 1, t)), 1, sp, lane);
    publish_norm(fmaxf(quad_norms(a0, 2, t), quad_norms(a1, 2, t)), 2, sp, lane);
    bar_sync(3, 256);
    if (tid == 0) mbar_arrive(bars + B_KVSTAGED * 8);
    p1_store_rows<0>(a0, 0, wg, w4, lane, sb);
    p1_store_rows<0>(a1, 1, wg, w4, lane, sb);
    fence_async_smem();
    publish_norm(fmaxf(quad_norms(a0, 0, t), quad_norms(a1, 0, t)), 0, sp, lane);
    bar_sync(3, 256);
    if (tid == 0) mbar_arrive(bars + B_P1DONE * 8);
}

__device__ __forceinline__ void exp_pack(const float (&s)[32], uint32_t (&p)[16]) {
    #pragma unroll
    for (int i = 0; i < 16; i++) p[i] = pack_bf16(ex2(s[2 * i]), ex2(s[2 * i + 1]));
}
__device__ __forceinline__ void qk_issue(float (&s)[32], uint64_t dq, uint64_t dk) {
    wg_ss_n64(s, dq, dk, 0);
    wg_ss_n64(s, dq + 2, dk + 2, 1);
}
__device__ __forceinline__ void pv_issue(float (&o)[20], const uint32_t (&p)[16], uint64_t dv) {
    #pragma unroll
    for (int k = 0; k < 4; k++) wg_rs_n40(o, p[4 * k], p[4 * k + 1], p[4 * k + 2], p[4 * k + 3], dv + 2 * k, 1);
}
__device__ __forceinline__ void online_exp_pack(float (&s)[32], uint32_t (&p)[16], float (&o)[20], float (&mx)[2]) {
    #pragma unroll
    for (int rr = 0; rr < 2; rr++) {
        float m = mx[rr];
        #pragma unroll
        for (int b = 0; b < 8; b++) m = fmaxf(m, fmaxf(s[4 * b + 2 * rr], s[4 * b + 2 * rr + 1]));
        m = fmaxf(m, __shfl_xor_sync(0xffffffffu, m, 1)); m = fmaxf(m, __shfl_xor_sync(0xffffffffu, m, 2));
        const float sc = ex2(mx[rr] - m);
        mx[rr] = m;
        #pragma unroll
        for (int b = 0; b < 5; b++) { o[4 * b + 2 * rr] *= sc; o[4 * b + 2 * rr + 1] *= sc; }
        #pragma unroll
        for (int b = 0; b < 8; b++) p[2 * b + rr] = pack_bf16(ex2(s[4 * b + 2 * rr] - m), ex2(s[4 * b + 2 * rr + 1] - m));
    }
}
__device__ __forceinline__ void attn_stage(const float (&o)[20], uint32_t base, int w4, int lane) {
    uint32_t vl[4], vh[4];
    pack32(o, 0, 0, 1.f / __shfl_sync(0xffffffffu, o[16], lane & ~3), vl);
    pack32(o, 0, 1, 1.f / __shfl_sync(0xffffffffu, o[18], lane & ~3), vh);
    const int mat = lane >> 3, row = w4 * 16 + (mat & 1) * 8 + (lane & 7);
    #pragma unroll
    for (int bp = 0; bp < 2; bp++)
        stsm4(base + row * 64 + (((2 * bp + (mat >> 1)) ^ ((row >> 1) & 3)) << 4), vl[2 * bp], vh[2 * bp], vl[2 * bp + 1], vh[2 * bp + 1]);
}

__device__ __forceinline__ bool scores_bounded(float nq, float nk, float nv) {
    return (nq * nk <= 3600.f) && (nv <= 1e24f) && (nq <= 1e18f) && (nk <= 1e18f);
}
__device__ __forceinline__ void attention(uint32_t sb, uint8_t* sp, int wg, int w4, int lane) {
    const uint32_t bars = sb + BAR_OFF;
    const bool elect = (w4 == 0 && lane == 0);
    const volatile float* nloc = (const volatile float*)(sp + NORM_OFF);
    #pragma unroll 1
    for (int task = 0; task < 2; task++) {
        bool fast = true;
        if (task == 0) fast = scores_bounded(nloc[0], nloc[2], nloc[4]);
        const uint64_t dqa = D_K64 | desc_lo(sb + Q_OFF + task * 16384 + wg * 8192), dqb = dqa + 256;
        float oa[20], ob[20], sa[32], sc[32];
        uint32_t pa[16], pb[16];
        #pragma unroll
        for (int i = 0; i < 20; i++) { oa[i] = 0.f; ob[i] = 0.f; }
        fence_regs(oa); fence_regs(ob);
        const uint64_t dkb = D_K64 | desc_lo(sb + KV_OFF), dvb = D_K128 | desc_lo(sb + KV_OFF + 8192);
        int body = 0;
        #pragma unroll 1
        for (; body < 8; body++) {
            if (body == (task == 0 ? 1 : 0)) {
                mbar_wait(bars + B_NORMOK * 8, 0);
                fast = fast && ((*((const volatile unsigned int*)(sp + NORM_OFF) + 8) >> task) & 1u);
            }
            if (!fast) break;
            const int s0 = (body & 1) * 2;
            const uint32_t par = (task * 4 + (body >> 1)) & 1;
            const uint64_t dk0 = dkb + s0 * (KV_STAGE >> 4), dv0 = dvb + s0 * (KV_STAGE >> 4);
            mbar_wait(bars + (B_KVFULL + s0) * 8, par);
            wg_fence();
            qk_issue(sa, dqa, dk0); wg_commit();
            qk_issue(sc, dqb, dk0); wg_commit();
            #pragma unroll
            for (int q = 0; q < 4; q++) {
                const int u = q >> 1, half = q & 1, qn = q + 1;
                const uint64_t dv = dv0 + u * (KV_STAGE >> 4) + half * (5120 >> 4);
                const uint64_t dkn = dk0 + (qn >> 1) * (KV_STAGE >> 4) + (qn & 1) * (4096 >> 4);
                wg_wait<1>();
                fence_regs(sa);
                exp_pack(sa, pa);
                if (q == 1) mbar_wait(bars + (B_KVFULL + s0 + 1) * 8, par);
                fence_regs(pa);
                wg_fence();
                pv_issue(oa, pa, dv);
                if (qn < 4) qk_issue(sa, dqa, dkn);
                wg_commit();
                wg_wait<1>();
                fence_regs(sc);
                if (q == 2) mbar_arrive_if(bars + (B_KVEMPTY + s0) * 8, elect);
                exp_pack(sc, pb);
                fence_regs(pb);
                wg_fence();
                pv_issue(ob, pb, dv);
                if (qn < 4) qk_issue(sc, dqb, dkn);
                wg_commit();
            }
            wg_wait<0>();
            fence_regs(oa); fence_regs(ob);
            mbar_arrive_if(bars + (B_KVEMPTY + s0 + 1) * 8, elect);
        }
        if (body < 8) {
            const float m0 = body > 0 ? 0.f : -INFINITY;
            float ma[2] = {m0, m0}, mb[2] = {m0, m0};
            #pragma unroll 1
            for (int q = body * 4; q < 32; q++) {
                const int u = (q >> 1) & 3, half = q & 1;
                const uint32_t par = (task * 4 + (q >> 3)) & 1;
                if (half == 0) mbar_wait(bars + (B_KVFULL + u) * 8, par);
                const uint64_t dk = dkb + u * (KV_STAGE >> 4) + half * (4096 >> 4);
                const uint64_t dv = dvb + u * (KV_STAGE >> 4) + half * (5120 >> 4);
                wg_fence();
                qk_issue(sa, dqa, dk);
                qk_issue(sc, dqb, dk);
                wg_commit();
                wg_wait<0>();
                fence_regs(sa); fence_regs(sc);
                online_exp_pack(sa, pa, oa, ma);
                online_exp_pack(sc, pb, ob, mb);
                fence_regs(pa); fence_regs(pb); fence_regs(oa); fence_regs(ob);
                wg_fence();
                pv_issue(oa, pa, dv);
                pv_issue(ob, pb, dv);
                wg_commit();
                wg_wait<0>();
                fence_regs(oa); fence_regs(ob);
                if (half == 1) mbar_arrive_if(bars + (B_KVEMPTY + u) * 8, elect);
            }
        }
        attn_stage(oa, sb + Q_OFF + task * 16384 + wg * 8192, w4, lane);
        attn_stage(ob, sb + Q_OFF + task * 16384 + wg * 8192 + 4096, w4, lane);
        fence_async_smem();
        __syncwarp();
        mbar_arrive_if(bars + (B_ODONE + wg) * 8, lane == 0);
    }
}

__device__ __forceinline__ void phase3(uint32_t sb, int wg, int w4, int lane, int c, const Params& P) {
    const uint32_t bars = sb + BAR_OFF;
    const bool elect = (w4 == 0 && lane == 0);
    float a0[64], a1[64];
    #pragma unroll 1
    for (int ks = 0; ks < 16; ks++) {
        const int s = ks & 3;
        mbar_wait(bars + (B_FULL3 + s) * 8, (ks >> 2) & 1);
        const uint32_t st = sb + s * R3_STAGE;
        const uint64_t db = desc_hi(8192, 1024, 1) | desc_lo(st + R3_A);
        const uint64_t da = D_K128 | desc_lo(st + wg * 8192);
        wg_fence();
        #pragma unroll
        for (int k = 0; k < 4; k++) {
            wg_ss_n128_tb(a0, da + k * 2, db + k * 128, (ks > 0 || k > 0) ? 1 : 0);
            wg_ss_n128_tb(a1, da + k * 2, db + 1024 + k * 128, (ks > 0 || k > 0) ? 1 : 0);
        }
        wg_commit();
        wg_wait<0>();
        mbar_arrive_if(bars + (B_EMPTY3 + s) * 8, elect);
    }
    fence_regs(a0); fence_regs(a1);
    const int br = c >> 6, rb = c & 15, cb = (c >> 4) & 3;
    bar_sync(3, 256);
    const uint32_t stg = sb + wg * 32768;
    const int mat = lane >> 3, row = w4 * 16 + (mat & 1) * 8 + (lane & 7);
    #pragma unroll
    for (int g = 0; g < 4; g++) {
        #pragma unroll
        for (int bp = 0; bp < 4; bp++) {
            const int b = (g & 1) * 8 + 2 * bp;
            const uint32_t ad = stg + g * 8192 + row * 128 + (((2 * bp + (mat >> 1)) ^ (lane & 7)) << 4);
            if (g < 2) stsm4(ad, pack_bf16(a0[4 * b], a0[4 * b + 1]), pack_bf16(a0[4 * b + 2], a0[4 * b + 3]), pack_bf16(a0[4 * b + 4], a0[4 * b + 5]), pack_bf16(a0[4 * b + 6], a0[4 * b + 7]));
            else stsm4(ad, pack_bf16(a1[4 * b], a1[4 * b + 1]), pack_bf16(a1[4 * b + 2], a1[4 * b + 3]), pack_bf16(a1[4 * b + 4], a1[4 * b + 5]), pack_bf16(a1[4 * b + 6], a1[4 * b + 7]));
        }
        fence_async_smem();
        bar_sync(1 + wg, 128);
        if (elect) { tma2d_store(&P.out, stg + g * 8192, br * 1024 + cb * 256 + g * 64, rb * 128 + wg * 64); bulk_commit(); }
    }
    if (elect) bulk_wait_all();
}

__device__ __forceinline__ uint32_t hmax2(uint32_t a, uint32_t b) { uint32_t r; asm("max.bf16x2 %0, %1, %2;" : "=r"(r) : "r"(a), "r"(b)); return r; }
__device__ __forceinline__ uint32_t hmin2(uint32_t a, uint32_t b) { uint32_t r; asm("min.bf16x2 %0, %1, %2;" : "=r"(r) : "r"(a), "r"(b)); return r; }
__device__ __forceinline__ float rcp(float x) { float y; asm("rcp.approx.ftz.f32 %0, %1;" : "=f"(y) : "f"(x)); return y; }
__device__ __forceinline__ void feature_map(const float (&px)[16], uint32_t (&F)[8][2]) {
    const float L2E = 1.4426950408889634f;
    #pragma unroll
    for (int rr = 0; rr < 2; rr++) {
        uint32_t pk[4];
        #pragma unroll
        for (int b = 0; b < 4; b++) pk[b] = pack_bf16(px[4 * b + 2 * rr], px[4 * b + 2 * rr + 1]);
        const uint32_t m2 = hmax2(hmax2(pk[0], pk[1]), hmax2(pk[2], pk[3]));
        const uint32_t n2 = hmin2(hmin2(pk[0], pk[1]), hmin2(pk[2], pk[3])) ^ 0x80008000u;
        uint32_t t = hmax2(__byte_perm(m2, n2, 0x5410), __byte_perm(m2, n2, 0x7632));
        t = hmax2(t, __shfl_xor_sync(0xffffffffu, t, 1));
        t = hmax2(t, __shfl_xor_sync(0xffffffffu, t, 2));
        const float nmx = -bf_lo(t) * L2E, pmn = -bf_hi(t) * L2E;
        float x[8];
        #pragma unroll
        for (int b = 0; b < 4; b++) { x[2 * b] = bf_lo(pk[b]); x[2 * b + 1] = bf_hi(pk[b]); }
        float ep[8], en[8], sp = 0.f, sn = 0.f;
        #pragma unroll
        for (int i = 0; i < 8; i++) {
            ep[i] = ex2(fmaf(x[i], L2E, nmx)); en[i] = ex2(fmaf(x[i], -L2E, pmn));
            sp += ep[i]; sn += en[i];
        }
        sp += __shfl_xor_sync(0xffffffffu, sp, 1); sn += __shfl_xor_sync(0xffffffffu, sn, 1);
        sp += __shfl_xor_sync(0xffffffffu, sp, 2); sn += __shfl_xor_sync(0xffffffffu, sn, 2);
        const float ip = rcp(sp), in = rcp(sn);
        #pragma unroll
        for (int b = 0; b < 4; b++) {
            F[b][rr] = pack_bf16(ep[2 * b] * ip, ep[2 * b + 1] * ip);
            F[4 + b][rr] = pack_bf16(en[2 * b] * in, en[2 * b + 1] * in);
        }
    }
}

__device__ __forceinline__ void a_epilogue(const float (&a)[96], uint32_t sb, int w4, int lane, int tile, int j) {
    uint32_t fk[8][2];
    const int mat = lane >> 3, i = lane & 7;
    const uint32_t scr = sb + SCR_OFF;
    {
        #pragma unroll
        for (int hh = 0; hh < 2; hh++) {
            uint32_t vl[4], vh[4];
            pack32(a, 16 + hh * 4, 0, 1.f, vl);
            pack32(a, 16 + hh * 4, 1, 1.f, vh);
            #pragma unroll
            for (int bp = 0; bp < 2; bp++) {
                const int rowd = 8 * (2 * bp + (mat >> 1)) + i, chunk = 2 * w4 + (mat & 1);
                stsm4_t(scr + 16384 + hh * 5120 + rowd * 128 + ((chunk ^ i) << 4), vl[2 * bp], vh[2 * bp], vl[2 * bp + 1], vh[2 * bp + 1]);
            }
        }
        #pragma unroll
        for (int kk = 0; kk < 4; kk++)
            g_qfrag[(size_t)(tile * 4 + kk) * 128 + w4 * 32 + lane] = make_uint4(pack_bf16(a[8 * kk], a[8 * kk + 1]), pack_bf16(a[8 * kk + 2], a[8 * kk + 3]),
                                                                                  pack_bf16(a[8 * kk + 4], a[8 * kk + 5]), pack_bf16(a[8 * kk + 6], a[8 * kk + 7]));
        #pragma unroll
        for (int b = 0; b < 8; b++) {
            fk[b][0] = pack_bf16(a[4 * (8 + b)], a[4 * (8 + b) + 1]); fk[b][1] = pack_bf16(a[4 * (8 + b) + 2], a[4 * (8 + b) + 3]);
        }
    }
    const uint64_t dw0 = D_K64 | desc_lo(sb + WPHI_OFF), dw1 = dw0 + 128;
    {
        float px0[16], px1[16];
        #pragma unroll
        for (int b = 0; b < 8; b++) fence_regs(fk[b]);
        wg_fence();
        wg_rs_n32(px0, fk[0][0], fk[0][1], fk[1][0], fk[1][1], dw0, 0);
        wg_rs_n32(px0, fk[2][0], fk[2][1], fk[3][0], fk[3][1], dw0 + 2, 1);
        wg_rs_n32(px1, fk[4][0], fk[4][1], fk[5][0], fk[5][1], dw1, 0);
        wg_rs_n32(px1, fk[6][0], fk[6][1], fk[7][0], fk[7][1], dw1 + 2, 1);
        wg_commit();
        wg_wait<0>();
        fence_regs(px0); fence_regs(px1);
        uint32_t F0[8][2], F1[8][2];
        feature_map(px0, F0);
        feature_map(px1, F1);
        #pragma unroll
        for (int bp = 0; bp < 4; bp++) {
            const int srow = w4 * 16 + (mat & 1) * 8 + i, chunk = 2 * bp + (mat >> 1);
            const uint32_t ad = scr + srow * 128 + ((chunk ^ i) << 4);
            stsm4(ad, F0[2 * bp][0], F0[2 * bp][1], F0[2 * bp + 1][0], F0[2 * bp + 1][1]);
            stsm4(ad + 8192, F1[2 * bp][0], F1[2 * bp][1], F1[2 * bp + 1][0], F1[2 * bp + 1][1]);
        }
    }
    fence_async_smem();
    bar_sync(4, 128);
    float kv0[20], kv1[20];
    {
        const uint64_t dA0 = desc_hi(8192, 1024, 1) | desc_lo(scr), dA1 = dA0 + 512;
        const uint64_t dB0 = D_K128 | desc_lo(scr + 16384), dB1 = dB0 + 320;
        wg_fence();
        #pragma unroll
        for (int k = 0; k < 4; k++) wg_ss_n40_ta(kv0, dA0 + k * 128, dB0 + k * 2, k > 0 ? 1 : 0);
        #pragma unroll
        for (int k = 0; k < 4; k++) wg_ss_n40_ta(kv1, dA1 + k * 128, dB1 + k * 2, k > 0 ? 1 : 0);
        wg_commit();
        wg_wait<0>();
        fence_regs(kv0); fence_regs(kv1);
    }
    #pragma unroll
    for (int hh = 0; hh < 2; hh++) {
        float* dst = g_kv + (size_t)((2 * j + hh) * 64 + w4 * 16 + (lane >> 2)) * 40 + (lane & 3) * 2;
        #pragma unroll
        for (int b = 0; b < 5; b++) {
            if (b < 4 || (lane & 3) == 0) {
                #pragma unroll
                for (int rr = 0; rr < 2; rr++) {
                    const float v0 = hh == 0 ? kv0[4 * b + 2 * rr] : kv1[4 * b + 2 * rr], v1 = hh == 0 ? kv0[4 * b + 2 * rr + 1] : kv1[4 * b + 2 * rr + 1];
                    asm volatile("red.global.add.v2.f32 [%0], {%1, %2};" :: "l"(dst + rr * 8 * 40 + b * 8), "f"(v0), "f"(v1) : "memory");
                }
            }
        }
    }
}

__device__ __forceinline__ void phi_q(const uint4 (&qf)[4], uint64_t dw0, uint64_t dw1, uint32_t (&F0)[8][2], uint32_t (&F1)[8][2]) {
    float px0[16], px1[16];
    uint32_t fq[16];
    #pragma unroll
    for (int q = 0; q < 4; q++) { fq[4 * q] = qf[q].x; fq[4 * q + 1] = qf[q].y; fq[4 * q + 2] = qf[q].z; fq[4 * q + 3] = qf[q].w; }
    fence_regs(fq);
    wg_fence();
    wg_rs_n32(px0, fq[0], fq[1], fq[2], fq[3], dw0, 0);
    wg_rs_n32(px0, fq[4], fq[5], fq[6], fq[7], dw0 + 2, 1);
    wg_rs_n32(px1, fq[8], fq[9], fq[10], fq[11], dw1, 0);
    wg_rs_n32(px1, fq[12], fq[13], fq[14], fq[15], dw1 + 2, 1);
    wg_commit();
    wg_wait<0>();
    fence_regs(px0); fence_regs(px1);
    feature_map(px0, F0);
    feature_map(px1, F1);
}

__device__ __forceinline__ void a_branch(uint32_t sb, uint8_t* sp, int w4, int lane, int r, int j, unsigned int epoch, const Params& P) {
    const uint32_t bars = sb + BAR_OFF;
    const int tid = w4 * 32 + lane;
    const bool elect = (tid == 0);
    for (int i = tid; i < 2 * 256; i += 128) {
        const int hh = i >> 8, w = i & 255;
        *(uint32_t*)(sp + SCR_OFF + 16384 + hh * 5120 + 4096 + w * 4) = (w < 32) ? 0x3F803F80u : 0u;
    }
    #pragma unroll 1
    for (int i = 0; i < 4; i++) {
        float a[96];
        #pragma unroll
        for (int q = 0; q < 96; q++) a[q] = 0.f;
        fence_regs(a);
        const uint64_t da0 = D_K128 | desc_lo(sb + GX_OFF), db0 = desc_hi(4096, 1024, 1) | desc_lo(sb);
        #pragma unroll 1
        for (int ks = 0; ks < 32; ks += 8) {
            #pragma unroll
            for (int u = 0; u < 8; u++) {
                mbar_wait(bars + (B_GFULL + (u & 3)) * 8, (u >> 2) & 1);
                const uint64_t da = da0 + (((u >> 1) & 3) * GX_STAGE + (u & 1) * 64 >> 4), db = db0 + ((u & 3) * GW_STAGE >> 4);
                wg_fence();
                wg_ss_n192_tb(a, da, db, 1);
                wg_ss_n192_tb(a, da + 2, db + 128, 1);
                wg_commit();
                wg_wait<1>();
                mbar_arrive_if(bars + (B_GEMPTY + ((u + 3) & 3)) * 8, elect && (u > 0 || ks > 0));
            }
        }
        wg_wait<0>();
        mbar_arrive_if(bars + (B_GEMPTY + 3) * 8, elect);
        fence_regs(a);
        if (i == 0) { if (elect) flag_wait(&g_cntB[j], 8 * (epoch + 1)); }
        bar_sync(4, 128);
        a_epilogue(a, sb, w4, lane, (r * 4 + i) * 16 + j, j);
    }
    bar_sync(4, 128);
    if (elect) mbar_arrive(bars + B_KVDONE * 8);
    const uint64_t dw0 = D_K64 | desc_lo(sb + WPHI_OFF), dw1 = dw0 + 128;
    uint32_t F0[8][2], F1[8][2];
    uint4 qf[4];
    #pragma unroll
    for (int q = 0; q < 4; q++) qf[q] = __ldcg(&g_qfrag[(size_t)(((r * 4) * 16 + j) * 4 + q) * 128 + tid]);
    phi_q(qf, dw0, dw1, F0, F1);
    #pragma unroll
    for (int q = 0; q < 4; q++) qf[q] = __ldcg(&g_qfrag[(size_t)(((r * 4 + 1) * 16 + j) * 4 + q) * 128 + tid]);
    if (elect) flag_wait(&g_cntA[j], 8 * (epoch + 1));
    bar_sync(4, 128);
    {
        const int hh = tid >> 6, fp = (tid >> 1) & 31, half = tid & 1, f = fp * 2;
        const float4* src0 = (const float4*)(g_kv + (size_t)((2 * j + hh) * 64 + f) * 40 + half * 20);
        float4 v0[5], v1[5];
        #pragma unroll
        for (int q = 0; q < 5; q++) { v0[q] = __ldcg(src0 + q); v1[q] = __ldcg(src0 + 10 + q); }
        #pragma unroll
        for (int q = 0; q < 5; q++) {
            const float e0[4] = {v0[q].x, v0[q].y, v0[q].z, v0[q].w}, e1[4] = {v1[q].x, v1[q].y, v1[q].z, v1[q].w};
            #pragma unroll
            for (int e = 0; e < 4; e++) {
                const int n = half * 20 + q * 4 + e;
                *(uint32_t*)(sp + SCR_OFF + hh * 5120 + n * 128 + (((f >> 3) ^ (n & 7)) << 4) + (f & 7) * 2) = n <= 32 ? pack_bf16(e0[e], e1[e]) : 0u;
            }
        }
    }
    fence_async_smem();
    bar_sync(4, 128);
    {
        const uint64_t dB0 = D_K128 | desc_lo(sb + SCR_OFF), dB1 = dB0 + 320;
        #pragma unroll 1
        for (int i = 0; i < 4; i++) {
            float o0[20], o1[20];
            #pragma unroll
            for (int b = 0; b < 8; b++) { fence_regs(F0[b]); fence_regs(F1[b]); }
            wg_fence();
            #pragma unroll
            for (int kk = 0; kk < 4; kk++) wg_rs_n40(o0, F0[2 * kk][0], F0[2 * kk][1], F0[2 * kk + 1][0], F0[2 * kk + 1][1], dB0 + 2 * kk, kk > 0 ? 1 : 0);
            #pragma unroll
            for (int kk = 0; kk < 4; kk++) wg_rs_n40(o1, F1[2 * kk][0], F1[2 * kk][1], F1[2 * kk + 1][0], F1[2 * kk + 1][1], dB1 + 2 * kk, kk > 0 ? 1 : 0);
            wg_commit();
            wg_wait<0>();
            fence_regs(o0); fence_regs(o1);
            #pragma unroll
            for (int hh = 0; hh < 2; hh++) {
                uint32_t vl[4];
                #pragma unroll
                for (int rr = 0; rr < 2; rr++) {
                    float den = __shfl_sync(0xffffffffu, hh == 0 ? o0[16 + 2 * rr] : o1[16 + 2 * rr], lane & ~3);
                    den = bf_round(bf_round(den) + 1e-6f);
                    const float inv = 1.f / den;
                    uint32_t v[4];
                    #pragma unroll
                    for (int b = 0; b < 4; b++) {
                        const uint32_t pk = hh == 0 ? pack_bf16(o0[4 * b + 2 * rr], o0[4 * b + 2 * rr + 1]) : pack_bf16(o1[4 * b + 2 * rr], o1[4 * b + 2 * rr + 1]);
                        v[b] = pack_bf16(bf_lo(pk) * inv, bf_hi(pk) * inv);
                    }
                    if (rr == 0) { vl[0] = v[0]; vl[1] = v[1]; vl[2] = v[2]; vl[3] = v[3]; }
                    else {
                        const int srow = (i & 1) * 64 + w4 * 16 + ((lane >> 3) & 1) * 8 + (lane & 7);
                        #pragma unroll
                        for (int bp = 0; bp < 2; bp++)
                            stsm4(sb + (i >> 1) * 16384 + srow * 128 + (((hh * 4 + 2 * bp + (lane >> 4)) ^ (lane & 7)) << 4), vl[2 * bp], v[2 * bp], vl[2 * bp + 1], v[2 * bp + 1]);
                    }
                }
            }
            if (i == 3) break;
            phi_q(qf, dw0, dw1, F0, F1);
            const int in = i + 2 < 4 ? i + 2 : 3;
            #pragma unroll
            for (int q = 0; q < 4; q++) qf[q] = __ldcg(&g_qfrag[(size_t)(((r * 4 + in) * 16 + j) * 4 + q) * 128 + tid]);
        }
    }
    fence_async_smem();
    bar_sync(4, 128);
    if (elect) {
        for (int u = 0; u < 2; u++) tma2d_store(&P.o, sb + u * 16384, j * 64, r * 256 + u * 128);
        bulk_commit();
        bulk_wait_all();
        mbar_arrive(bars + B_ADONE * 8);
        asm volatile("fence.proxy.async.global;" ::: "memory");
        flag_signal_relaxed(&g_cntOA[r]);
    }
}

__global__ void __launch_bounds__(512, 1) fused_kernel(const __grid_constant__ Params P) {
    extern __shared__ uint8_t smem_raw[];
    const uint32_t sb = (smem_u32(smem_raw) + 1023) & ~1023u;
    uint8_t* sp = smem_raw + (sb - smem_u32(smem_raw));
    const uint32_t bars = sb + BAR_OFF;
    const int c = blockIdx.x, r = c & 7, j = c >> 3;
    if (threadIdx.x == 384) {
        for (int s = 0; s < R1_N; s++) { mbar_init(bars + (B_FULL1 + s) * 8, 1); mbar_init(bars + (B_EMPTY1 + s) * 8, 2); }
        asm volatile("fence.mbarrier_init.release.cluster;" ::: "memory");
        fence_async_smem();
        for (int ks = 0; ks < R1_N; ks++) {
            const uint32_t st = sb + ks * R1_STAGE, fb = bars + (B_FULL1 + ks) * 8;
            mbar_expect_tx(fb, R1_STAGE);
            tma2d(st, &P.xB, ks * 64, r * 256, fb);
            tma3d(st + R1_A, &P.wB, j * 64, ks * 64, 0, fb);
        }
    }
    if (threadIdx.x < 120) {
        const int i = threadIdx.x;
        const char* src = i < 48 ? (const char*)P.pxB + (size_t)(r * 256 + j * 16 + i / 3) * 2048 + (i % 3) * 128
                                 : (const char*)P.pwB + (size_t)(r * 24 + (i - 48) / 3) * 6144 + ((i - 48) % 3) * 2048 + j * 128;
        asm volatile("prefetch.global.L2 [%0];" :: "l"(src));
    }
    const int warp = __shfl_sync(0xffffffffu, (int)(threadIdx.x >> 5), 0), lane = threadIdx.x & 31, wg = warp >> 2, w4 = warp & 3;
    const unsigned int epoch = __ldcg(&g_epoch[c]);
    if (threadIdx.x == 416) { prefetch_map(&P.xA); prefetch_map(&P.wA); prefetch_map(&P.o); prefetch_map(&P.oS); prefetch_map(&P.woA); prefetch_map(&P.woB); prefetch_map(&P.out); }
    if (threadIdx.x == 0) {
        for (int s = 0; s < KV_N; s++) { mbar_init(bars + (B_KVFULL + s) * 8, 1); mbar_init(bars + (B_KVEMPTY + s) * 8, 2); }
        for (int s = 0; s < G_N; s++) { mbar_init(bars + (B_GFULL + s) * 8, 1); mbar_init(bars + (B_GEMPTY + s) * 8, 1); }
        for (int q = 0; q < 6; q++) *((unsigned int*)(sp + NORM_OFF) + q) = 0u;
    }
    if (threadIdx.x == 32) {
        for (int s = 0; s < R3_N; s++) { mbar_init(bars + (B_FULL3 + s) * 8, 1); mbar_init(bars + (B_EMPTY3 + s) * 8, 2); }
        mbar_init(bars + B_R1FREE * 8, 1); mbar_init(bars + B_P1DONE * 8, 1); mbar_init(bars + B_P2DONE * 8, 2); mbar_init(bars + B_ADONE * 8, 1);
        mbar_init(bars + B_NORMOK * 8, 1); mbar_init(bars + B_ODONE * 8, 4); mbar_init(bars + (B_ODONE + 1) * 8, 4);
        mbar_init(bars + B_KVDONE * 8, 1); mbar_init(bars + B_KVSTAGED * 8, 1);
    }
    if (threadIdx.x == 0 || threadIdx.x == 32) asm volatile("fence.mbarrier_init.release.cluster;" ::: "memory");
    __syncthreads();

    if (wg == 3) {
        reg_dealloc<24>();
        if (warp == 12) {
            for (int ks = R1_N; ks < 16; ks++) {
                const int s = ks % R1_N;
                mbar_wait(bars + (B_EMPTY1 + s) * 8, ((ks / R1_N) - 1) & 1);
                const uint32_t st = sb + s * R1_STAGE, fb = bars + (B_FULL1 + s) * 8;
                if (elect_one()) {
                    mbar_expect_tx(fb, R1_STAGE);
                    tma2d(st, &P.xB, ks * 64, r * 256, fb);
                    tma3d(st + R1_A, &P.wB, j * 64, ks * 64, 0, fb);
                    if (ks >= 3 && ks < 13) {
                        const int q = ks - 3;
                        const char* src = q < 6 ? (const char*)P.pwA + (size_t)c * 49152 + q * 8192 : (const char*)P.pxA + (size_t)c * 32768 + (q - 6) * 8192;
                        asm volatile("cp.async.bulk.prefetch.L2.global [%0], %1;" :: "l"(src), "r"(8192u) : "memory");
                    }
                }
                __syncwarp();
            }
            mbar_wait_long(bars + B_KVSTAGED * 8, 0);
            if (lane == 0) {
                for (int q = 0; q < 4; q++) {
                    const int hh = q >> 1, w = q & 1;
                    const uint32_t st = sb + KV_OFF + q * KV_STAGE;
                    bulk_store(&g_kimg[(size_t)((2 * j + hh) * 16 + 2 * r + w) * 512], st, 8192);
                    bulk_store(&g_vimg[(size_t)((2 * j + hh) * 32 + (2 * r + w) * 2) * 256], st + 8192, 4096);
                    bulk_store(&g_vimg[(size_t)((2 * j + hh) * 32 + (2 * r + w) * 2 + 1) * 256], st + 8192 + 5120, 4096);
                    if (q & 1) bulk_commit();
                }
                {
                    float chk = 0.f;
                    for (int q = 0; q < 4; q++) {
                        float* dst = &g_norm[((q >> 1) * NH + 2 * j + (q & 1)) * 8 + r];
                        asm volatile("st.relaxed.gpu.global.f32 [%0], %1;" :: "l"(dst), "f"(__uint_as_float(*((volatile unsigned int*)(sp + NORM_OFF) + 2 + q))) : "memory");
                        float v; asm volatile("ld.relaxed.gpu.global.f32 %0, [%1];" : "=f"(v) : "l"(dst) : "memory");
                        chk += v;
                    }
                    asm volatile("" :: "f"(chk) : "memory");
                }
                asm volatile("cp.async.bulk.wait_group 1;" ::: "memory");
                asm volatile("fence.proxy.async.global;" ::: "memory");
                flag_signal_relaxed(&g_cntB[j]);
                asm volatile("cp.async.bulk.wait_group.read 0;" ::: "memory");
                flag_wait(&g_cntB[j], 8 * (epoch + 1));
                asm volatile("fence.proxy.async.global;" ::: "memory");
            }
            __syncwarp();
            for (int g = 2; g < 32; g++) {
                const int s = g & 3, h = 2 * j + (g >> 4), t = (2 * r + g) & 15;
                if (g >= KV_N) mbar_wait_long(bars + (B_KVEMPTY + s) * 8, ((g >> 2) - 1) & 1);
                const uint32_t st = sb + KV_OFF + s * KV_STAGE, fb = bars + (B_KVFULL + s) * 8;
                if (elect_one()) {
                    mbar_expect_tx(fb, 16384);
                    bulk_load(st, &g_kimg[(size_t)(h * 16 + t) * 512], 8192, fb);
                    bulk_load(st + 8192, &g_vimg[(size_t)(h * 32 + 2 * t) * 256], 4096, fb);
                    bulk_load(st + 8192 + 5120, &g_vimg[(size_t)(h * 32 + 2 * t + 1) * 256], 4096, fb);
                    if (g >= 8 && g < 12) {
                        const char* src = (g < 10 ? (const char*)P.pwoA : (const char*)P.pwoB) + (size_t)c * 16384 + (g & 1) * 8192;
                        asm volatile("cp.async.bulk.prefetch.L2.global [%0], %1;" :: "l"(src), "r"(8192u) : "memory");
                    }
                }
                __syncwarp();
                if (g == 3) {
                    if (lane == 0) {
                        bulk_wait_all();
                        asm volatile("fence.proxy.async.global;" ::: "memory");
                        flag_signal_relaxed(&g_cntB[16 + j]);
                    }
                    __syncwarp();
                }
                if (g == 15) {
                    if (lane == 0) { flag_wait(&g_cntB[16 + j], 8 * (epoch + 1)); asm volatile("fence.proxy.async.global;" ::: "memory"); }
                    __syncwarp();
                }
            }
            const int br = c >> 6, rb = c & 15, cb = (c >> 4) & 3;
            for (int ks = 0; ks < 16; ks++) {
                const int s = ks & 3;
                if (ks == 0) {
                    mbar_wait_long(bars + B_ADONE * 8, 0);
                    if (lane == 0) {
                        if (br == 0) flag_wait(&g_cntOA[rb >> 1], 16 * (epoch + 1)); else flag_wait(&g_cntOB[rb >> 1], 32 * (epoch + 1));
                        asm volatile("fence.proxy.async.global;" ::: "memory");
                    }
                    __syncwarp();
                }
                if (ks == 1) mbar_wait(bars + (B_KVEMPTY + 0) * 8, 1);
                if (ks == 2) { mbar_wait(bars + (B_KVEMPTY + 1) * 8, 1); mbar_wait(bars + (B_KVEMPTY + 2) * 8, 1); mbar_wait(bars + (B_KVEMPTY + 3) * 8, 1); }
                if (ks == 3) mbar_wait(bars + B_P2DONE * 8, 0);
                if (ks == 8 && br == 1) {
                    if (lane == 0) { flag_wait(&g_cntOB[8 + (rb >> 1)], 32 * (epoch + 1)); asm volatile("fence.proxy.async.global;" ::: "memory"); }
                    __syncwarp();
                }
                if (ks >= R3_N) mbar_wait(bars + (B_EMPTY3 + s) * 8, ((ks >> 2) - 1) & 1);
                const uint32_t st = sb + s * R3_STAGE, fb = bars + (B_FULL3 + s) * 8;
                if (elect_one()) {
                    mbar_expect_tx(fb, R3_STAGE);
                    tma2d(st, &P.o, ks * 64, br * SEQ + rb * 128, fb);
                    if (br == 0) tma3d(st + R3_A, &P.woA, 0, ks * 64, cb * 4, fb);
                    else tma5d(st + R3_A, &P.woB, 0, 0, ks >> 3, 2 * (ks & 7), cb * 4, fb);
                }
                __syncwarp();
            }
        } else if (warp == 13) {
            mbar_wait_long(bars + B_R1FREE * 8, 0);
            for (int it = 0; it < 128; it++) {
                const int s = it & 3, i = it >> 5, ks = it & 31;
                if (it >= G_N) mbar_wait(bars + (B_GEMPTY + s) * 8, ((it >> 2) - 1) & 1);
                const uint32_t fb = bars + (B_GFULL + s) * 8;
                if (elect_one()) {
                    mbar_expect_tx(fb, (it & 1) ? GW_STAGE : GW_STAGE + GX_STAGE);
                    if (!(it & 1)) tma2d(sb + GX_OFF + ((it >> 1) & 3) * GX_STAGE, &P.xA, ks * 32, r * 256 + i * 64, fb);
                    tma3d(sb + s * GW_STAGE, &P.wA, j * 64, ks * 32, 0, fb);
                }
                __syncwarp();
            }
        } else if (warp == 15) {
            if (lane == 0) {
                for (int q = 0; q < 4; q++) {
                    const int w = q & 1, task = q >> 1;
                    mbar_wait_long(bars + (B_ODONE + w) * 8, task);
                    tma2d_store(&P.oS, sb + Q_OFF + task * 16384 + w * 8192, task * 512 + j * 32, SEQ + r * 256 + w * 128);
                    bulk_commit();
                    bulk_wait_all();
                    if (task == 1) mbar_arrive(bars + B_P2DONE * 8);
                    asm volatile("fence.proxy.async.global;" ::: "memory");
                    flag_signal_relaxed(&g_cntOB[task * 8 + r]);
                }
            }
        } else {
            mbar_wait_long(bars + B_R1FREE * 8, 0);
            for (int i = lane; i < KV_N * 2 * 64; i += 32) {
                const int w = i & 63;
                *(uint4*)(sp + KV_OFF + (i >> 7) * KV_STAGE + 8192 + ((i >> 6) & 1) * 5120 + 4096 + w * 16) =
                    w < 8 ? make_uint4(0x3F803F80u, 0x3F803F80u, 0x3F803F80u, 0x3F803F80u) : make_uint4(0u, 0u, 0u, 0u);
            }
            fence_async_smem();
            __syncwarp();
            if (lane == 0) {
                mbar_wait(bars + B_KVSTAGED * 8, 0);
                mbar_arrive(bars + (B_KVFULL + 0) * 8);
                mbar_arrive(bars + (B_KVFULL + 1) * 8);
                flag_wait(&g_cntB[j], 8 * (epoch + 1));
            }
            __syncwarp();
            {
                float v = __ldcg(&g_norm[((lane >> 4) * NH + 2 * j + ((lane >> 3) & 1)) * 8 + (lane & 7)]);
                v = fmaxf(v, __shfl_xor_sync(0xffffffffu, v, 1)); v = fmaxf(v, __shfl_xor_sync(0xffffffffu, v, 2)); v = fmaxf(v, __shfl_xor_sync(0xffffffffu, v, 4));
                const float nk0 = __shfl_sync(0xffffffffu, v, 0), nk1 = __shfl_sync(0xffffffffu, v, 8), nv0 = __shfl_sync(0xffffffffu, v, 16), nv1 = __shfl_sync(0xffffffffu, v, 24);
                mbar_wait(bars + B_P1DONE * 8, 0);
                if (lane == 0) {
                    const volatile float* nloc = (const volatile float*)(sp + NORM_OFF);
                    *((volatile unsigned int*)(sp + NORM_OFF) + 8) = (scores_bounded(nloc[0], nk0, nv0) ? 1u : 0u) | (scores_bounded(nloc[1], nk1, nv1) ? 2u : 0u);
                    mbar_arrive(bars + B_NORMOK * 8);
                    mbar_wait_long(bars + B_KVDONE * 8, 0);
                    flag_signal(&g_cntA[j]);
                }
            }
        }
    } else if (wg == 2) {
        reg_dealloc<24>();
        for (int i = threadIdx.x & 127; i < 2048; i += 128) {
            const int hh = i >> 10, d = (i >> 5) & 31, f = i & 31;
            *(__nv_bfloat16*)(sp + WPHI_OFF + hh * 2048 + f * 64 + (((d >> 3) ^ ((f >> 1) & 3)) << 4) + (d & 7) * 2) = P.wphi[(size_t)(2 * j + hh) * 1024 + d * 32 + f];
        }
        fence_async_smem();
        mbar_wait_long(bars + B_P1DONE * 8, 0);
        reg_alloc<152>();
        a_branch(sb, sp, w4, lane, r, j, epoch, P);
    } else {
        reg_alloc<232>();
        if (r == 0) {
            float4* z = (float4*)(g_kv + (size_t)2 * j * 64 * 40);
            for (int i = threadIdx.x; i < 2 * 64 * 40 / 4; i += 256) z[i] = make_float4(0.f, 0.f, 0.f, 0.f);
            __threadfence();
        }
        phase1(sb, sp, wg, w4, lane);
        reg_dealloc<168>();
        attention(sb, sp, wg, w4, lane);
        phase3(sb, wg, w4, lane, c, P);
        if (threadIdx.x == 0) g_epoch[c] = epoch + 1;
    }
}

typedef CUresult (*EncodeFn)(CUtensorMap*, CUtensorMapDataType, cuuint32_t, void*, const cuuint64_t*, const cuuint64_t*, const cuuint32_t*,
                             const cuuint32_t*, CUtensorMapInterleave, CUtensorMapSwizzle, CUtensorMapL2promotion, CUtensorMapFloatOOBfill);
static void make_map(EncodeFn enc, CUtensorMap* m, const void* ptr, uint64_t inner, uint64_t outer, uint32_t box_inner, uint32_t box_outer, CUtensorMapSwizzle swz) {
    cuuint64_t gd[2] = {inner, outer}; cuuint64_t gs[1] = {inner * 2}; cuuint32_t bd[2] = {box_inner, box_outer}; cuuint32_t es[2] = {1, 1};
    enc(m, CU_TENSOR_MAP_DATA_TYPE_BFLOAT16, 2, const_cast<void*>(ptr), gd, gs, bd, es, CU_TENSOR_MAP_INTERLEAVE_NONE, swz,
        CU_TENSOR_MAP_L2_PROMOTION_L2_128B, CU_TENSOR_MAP_FLOAT_OOB_FILL_NONE);
}

struct Dims { uint64_t v[5]; };
static void make_map_nd(EncodeFn enc, CUtensorMap* m, const void* ptr, int rank, Dims dims, Dims strides, Dims box) {
    cuuint64_t gd[5], gs[5]; cuuint32_t bd[5], es[5];
    for (int i = 0; i < 5; i++) { gd[i] = dims.v[i]; gs[i] = strides.v[i]; bd[i] = (cuuint32_t)box.v[i]; es[i] = 1; }
    enc(m, CU_TENSOR_MAP_DATA_TYPE_BFLOAT16, rank, const_cast<void*>(ptr), gd, gs, bd, es, CU_TENSOR_MAP_INTERLEAVE_NONE, CU_TENSOR_MAP_SWIZZLE_128B,
        CU_TENSOR_MAP_L2_PROMOTION_L2_128B, CU_TENSOR_MAP_FLOAT_OOB_FILL_NONE);
}

}

extern "C" void kernel_launch(void* const* d_in, const int* in_sizes, int n_in, void* d_out, int out_size) {
    using namespace hk;
    (void)in_sizes; (void)n_in; (void)out_size;
    const __nv_bfloat16* A_x = (const __nv_bfloat16*)d_in[0];
    const __nv_bfloat16* A_wqkv = (const __nv_bfloat16*)d_in[1];
    const __nv_bfloat16* A_wphi = (const __nv_bfloat16*)d_in[2];
    const __nv_bfloat16* A_wo = (const __nv_bfloat16*)d_in[3];
    const __nv_bfloat16* B_x = (const __nv_bfloat16*)d_in[4];
    const __nv_bfloat16* B_wqkv = (const __nv_bfloat16*)d_in[5];
    const __nv_bfloat16* B_wo = (const __nv_bfloat16*)d_in[6];
    static EncodeFn enc = nullptr;
    static void* p_o = nullptr;
    if (!enc) {
        void* fn = nullptr; cudaDriverEntryPointQueryResult qr;
        cudaGetDriverEntryPoint("cuTensorMapEncodeTiled", &fn, cudaEnableDefault, &qr);
        enc = (EncodeFn)fn;
        cudaGetSymbolAddress(&p_o, g_o);
        cudaFuncSetAttribute(fused_kernel, cudaFuncAttributeMaxDynamicSharedMemorySize, SMEM_BYTES);
    }
    Params P;
    const CUtensorMapSwizzle S128 = CU_TENSOR_MAP_SWIZZLE_128B, S64 = CU_TENSOR_MAP_SWIZZLE_64B;
    make_map(enc, &P.xB, B_x, DM, SEQ, 64, 256, S128);
    make_map_nd(enc, &P.wB, B_wqkv, 3, {DM, DM, 3}, {3 * DM * 2, DM * 2}, {64, 64, 3});
    make_map(enc, &P.xA, A_x, DM, SEQ, 64, 64, S128);
    make_map_nd(enc, &P.wA, A_wqkv, 3, {DM, DM, 3}, {3 * DM * 2, DM * 2}, {64, 32, 3});

    make_map(enc, &P.o, p_o, DM, 2 * SEQ, 64, 128, S128);
    make_map(enc, &P.oS, p_o, DM, 2 * SEQ, 32, 128, S64);
    make_map_nd(enc, &P.woA, A_wo, 3, {64, DM, 16}, {DM * 2, 128}, {64, 64, 4});
    make_map_nd(enc, &P.woB, B_wo, 5, {64, 32, 2, 16, 16}, {DM * 2, 32 * DM * 2, 64 * DM * 2, 128}, {64, 32, 1, 2, 4});

    P.pxB = B_x; P.pwB = B_wqkv; P.pxA = A_x; P.pwA = A_wqkv; P.pwoA = A_wo; P.pwoB = B_wo; P.wphi = A_wphi;
    make_map(enc, &P.out, d_out, 2 * DM, SEQ, 64, 64, S128);
    fused_kernel<<<128, 512, SMEM_BYTES, cudaStreamPerThread>>>(P);
}
```

```cpp
#include <cuda_runtime.h>
#include <cuda_bf16.h>
#include <cuda.h>
#include <stdint.h>

namespace hk {

constexpr int SEQ = 2048, DM = 1024, NH = 32;

__device__ uint4 g_kimg[NH * 16 * 512];
__device__ uint4 g_vimg[NH * 32 * 256];
__device__ __nv_bfloat16 g_o[2 * SEQ * DM];
__device__ uint4 g_qfrag[512 * 4 * 128];
__device__ float g_kv[NH * 64 * 40];
__device__ float g_norm[2 * NH * 8];
__device__ unsigned int g_cntB[32], g_cntA[16], g_cntOA[8], g_cntOB[16];
__device__ unsigned int g_epoch[128];

struct Params {
    CUtensorMap xB, wB, xA, wA, o, oS, woA, woB, out;
    const __nv_bfloat16 *pxB, *pwB, *pxA, *pwA, *pwoA, *pwoB, *wphi;
};

constexpr int R1_A = 256 * 64 * 2, R1_B = 192 * 64 * 2, R1_STAGE = R1_A + R1_B, R1_N = 3;
constexpr int GW_STAGE = 12288, G_N = 4, GX_OFF = G_N * GW_STAGE, GX_STAGE = 8192;
constexpr int KV_OFF = GX_OFF + 4 * GX_STAGE, KV_STAGE = 18432, KV_N = 4;
constexpr int Q_OFF = KV_OFF + KV_N * KV_STAGE;
constexpr int SCR_OFF = Q_OFF + 32768;
constexpr int WPHI_OFF = SCR_OFF + 26624;
constexpr int BAR_OFF = WPHI_OFF + 4096;
constexpr int R3_A = 128 * 64 * 2, R3_STAGE = R3_A + 256 * 64 * 2, R3_N = 4;
constexpr int SMEM_BYTES = BAR_OFF + 1024 + 1024;
static_assert(R3_N * R3_STAGE <= WPHI_OFF, "ring3");
static_assert(SMEM_BYTES <= 232448, "smem");
constexpr int B_FULL1 = 0, B_EMPTY1 = 3, B_KVFULL = 6, B_KVEMPTY = 10, B_GFULL = 16, B_GEMPTY = 21, B_FULL3 = 26, B_EMPTY3 = 30,
              B_R1FREE = 34, B_P1DONE = 35, B_P2DONE = 36, B_NORMOK = 37, B_ODONE = 38, B_KVDONE = 40, B_ADONE = 41, B_KVSTAGED = 42;
constexpr int NORM_OFF = BAR_OFF + 512;

__device__ __forceinline__ uint32_t smem_u32(const void* p) { return (uint32_t)__cvta_generic_to_shared(p); }
__device__ __forceinline__ void mbar_init(uint32_t bar, uint32_t cnt) { asm volatile("mbarrier.init.shared::cta.b64 [%0], %1;" :: "r"(bar), "r"(cnt) : "memory"); }
__device__ __forceinline__ void mbar_expect_tx(uint32_t bar, uint32_t bytes) { asm volatile("mbarrier.arrive.expect_tx.shared::cta.b64 _, [%0], %1;" :: "r"(bar), "r"(bytes) : "memory"); }
__device__ __forceinline__ void mbar_arrive(uint32_t bar) { asm volatile("mbarrier.arrive.shared::cta.b64 _, [%0];" :: "r"(bar) : "memory"); }
__device__ __forceinline__ void mbar_arrive_if(uint32_t bar, bool pred) {
    asm volatile("{\n.reg .pred p;\nsetp.ne.u32 p, %1, 0;\n@p mbarrier.arrive.shared::cta.b64 _, [%0];\n}\n" :: "r"(bar), "r"((uint32_t)pred) : "memory");
}
__device__ __forceinline__ void mbar_wait(uint32_t bar, uint32_t parity) {
    asm volatile("{\n.reg .pred p;\n.reg .u32 c;\nmov.u32 c, 0;\nLAB_WAIT:\nmbarrier.try_wait.parity.shared::cta.b64 p, [%0], %1;\n@p bra LAB_DONE;\n"
                 "add.u32 c, c, 1;\nsetp.lt.u32 p, c, 4194304;\n@p bra LAB_WAIT;\ntrap;\nLAB_DONE:\n}\n" :: "r"(bar), "r"(parity) : "memory");
}
__device__ __forceinline__ void mbar_wait_long(uint32_t bar, uint32_t parity) {
    asm volatile("{\n.reg .pred p;\n.reg .u32 c;\nmov.u32 c, 0;\nLAB_WAIT:\nmbarrier.try_wait.parity.shared::cta.b64 p, [%0], %1, 100000;\n@p bra LAB_DONE;\n"
                 "add.u32 c, c, 1;\nsetp.lt.u32 p, c, 262144;\n@p bra LAB_WAIT;\ntrap;\nLAB_DONE:\n}\n" :: "r"(bar), "r"(parity) : "memory");
}
__device__ __forceinline__ void flag_wait(const unsigned int* cnt, unsigned int target) {
    asm volatile("{\n.reg .pred p;\n.reg .u32 c, v;\nmov.u32 c, 0;\nLAB_WAIT:\nld.acquire.gpu.global.u32 v, [%0];\nsub.u32 v, v, %1;\nsetp.ge.s32 p, v, 0;\n@p bra LAB_DONE;\n"
                 "nanosleep.u32 64;\nadd.u32 c, c, 1;\nsetp.lt.u32 p, c, 4194304;\n@p bra LAB_WAIT;\ntrap;\nLAB_DONE:\n}\n" :: "l"(cnt), "r"(target) : "memory");
}
__device__ __forceinline__ void flag_signal(unsigned int* cnt) {
    asm volatile("red.release.gpu.global.add.u32 [%0], 1;" :: "l"(cnt) : "memory");
}
__device__ __forceinline__ void flag_signal_relaxed(unsigned int* cnt) {
    asm volatile("red.relaxed.gpu.global.add.u32 [%0], 1;" :: "l"(cnt) : "memory");
}
__device__ __forceinline__ void tma2d(uint32_t dst, const CUtensorMap* m, int c0, int c1, uint32_t bar) {
    asm volatile("cp.async.bulk.tensor.2d.shared::cluster.global.mbarrier::complete_tx::bytes [%0], [%1, {%3, %4}], [%2];"
                 :: "r"(dst), "l"(m), "r"(bar), "r"(c0), "r"(c1) : "memory");
}
__device__ __forceinline__ void tma3d(uint32_t dst, const CUtensorMap* m, int c0, int c1, int c2, uint32_t bar) {
    asm volatile("cp.async.bulk.tensor.3d.shared::cluster.global.mbarrier::complete_tx::bytes [%0], [%1, {%3, %4, %5}], [%2];"
                 :: "r"(dst), "l"(m), "r"(bar), "r"(c0), "r"(c1), "r"(c2) : "memory");
}
__device__ __forceinline__ void tma5d(uint32_t dst, const CUtensorMap* m, int c0, int c1, int c2, int c3, int c4, uint32_t bar) {
    asm volatile("cp.async.bulk.tensor.5d.shared::cluster.global.mbarrier::complete_tx::bytes [%0], [%1, {%3, %4, %5, %6, %7}], [%2];"
                 :: "r"(dst), "l"(m), "r"(bar), "r"(c0), "r"(c1), "r"(c2), "r"(c3), "r"(c4) : "memory");
}
__device__ __forceinline__ bool elect_one() {
    uint32_t p;
    asm volatile("{\n.reg .pred P;\nelect.sync _|P, 0xffffffff;\nselp.u32 %0, 1, 0, P;\n}\n" : "=r"(p));
    return p != 0;
}
__device__ __forceinline__ void prefetch_map(const CUtensorMap* m) { asm volatile("prefetch.tensormap [%0];" :: "l"(m) : "memory"); }
__device__ __forceinline__ void tma2d_store(const CUtensorMap* m, uint32_t src, int c0, int c1) {
    asm volatile("cp.async.bulk.tensor.2d.global.shared::cta.bulk_group [%0, {%2, %3}], [%1];" :: "l"(m), "r"(src), "r"(c0), "r"(c1) : "memory");
}
__device__ __forceinline__ void bulk_load(uint32_t dst, const void* src, uint32_t bytes, uint32_t bar) {
    asm volatile("cp.async.bulk.shared::cluster.global.mbarrier::complete_tx::bytes [%0], [%1], %2, [%3];" :: "r"(dst), "l"(src), "r"(bytes), "r"(bar) : "memory");
}
__device__ __forceinline__ void bulk_store(void* dst, uint32_t src, uint32_t bytes) {
    asm volatile("cp.async.bulk.global.shared::cta.bulk_group [%0], [%1], %2;" :: "l"(dst), "r"(src), "r"(bytes) : "memory");
}
__device__ __forceinline__ void bulk_commit() { asm volatile("cp.async.bulk.commit_group;" ::: "memory"); }
__device__ __forceinline__ void bulk_wait_all() { asm volatile("cp.async.bulk.wait_group 0;" ::: "memory"); }
__device__ __forceinline__ void fence_async_smem() { asm volatile("fence.proxy.async.shared::cta;" ::: "memory"); }
__device__ __forceinline__ void fence_async_all() { asm volatile("fence.proxy.async;" ::: "memory"); }
__device__ __forceinline__ void wg_fence() { asm volatile("wgmma.fence.sync.aligned;" ::: "memory"); }
__device__ __forceinline__ void wg_commit() { asm volatile("wgmma.commit_group.sync.aligned;" ::: "memory"); }
template <int N> __device__ __forceinline__ void wg_wait() { asm volatile("wgmma.wait_group.sync.aligned %0;" :: "n"(N) : "memory"); }
__device__ __forceinline__ void bar_sync(int id, int n) { asm volatile("bar.sync %0, %1;" :: "r"(id), "r"(n) : "memory"); }
template <int N> __device__ __forceinline__ void reg_alloc() { asm volatile("setmaxnreg.inc.sync.aligned.u32 %0;" :: "n"(N)); }
template <int N> __device__ __forceinline__ void reg_dealloc() { asm volatile("setmaxnreg.dec.sync.aligned.u32 %0;" :: "n"(N)); }
__device__ __forceinline__ void stsm4(uint32_t addr, uint32_t r0, uint32_t r1, uint32_t r2, uint32_t r3) {
    asm volatile("stmatrix.sync.aligned.m8n8.x4.shared.b16 [%0], {%1, %2, %3, %4};" :: "r"(addr), "r"(r0), "r"(r1), "r"(r2), "r"(r3) : "memory");
}
__device__ __forceinline__ void stsm4_t(uint32_t addr, uint32_t r0, uint32_t r1, uint32_t r2, uint32_t r3) {
    asm volatile("stmatrix.sync.aligned.m8n8.x4.trans.shared.b16 [%0], {%1, %2, %3, %4};" :: "r"(addr), "r"(r0), "r"(r1), "r"(r2), "r"(r3) : "memory");
}
__host__ __device__ constexpr uint64_t desc_hi(uint32_t lbo, uint32_t sbo, int swz) {
    return ((uint64_t)((lbo & 0x3FFFF) >> 4) << 16) | ((uint64_t)((sbo & 0x3FFFF) >> 4) << 32) | ((uint64_t)swz << 62);
}
__device__ __forceinline__ uint64_t desc_lo(uint32_t addr) { return (uint64_t)((addr & 0x3FFFF) >> 4); }
constexpr uint64_t D_K128 = desc_hi(16, 1024, 1);
constexpr uint64_t D_K64 = desc_hi(16, 512, 2);
__device__ __forceinline__ uint32_t pack_bf16(float lo, float hi) {
    uint32_t r; asm("cvt.rn.bf16x2.f32 %0, %1, %2;" : "=r"(r) : "f"(hi), "f"(lo)); return r;
}
__device__ __forceinline__ float bf_lo(uint32_t r) { return __uint_as_float(r << 16); }
__device__ __forceinline__ float bf_hi(uint32_t r) { return __uint_as_float(r & 0xFFFF0000u); }
__device__ __forceinline__ float bf_round(float x) { return __bfloat162float(__float2bfloat16_rn(x)); }
__device__ __forceinline__ float ex2(float x) { float y; asm("ex2.approx.ftz.f32 %0, %1;" : "=f"(y) : "f"(x)); return y; }
template <int R> __device__ __forceinline__ void fence_regs(float (&d)[R]) {
    #pragma unroll
    for (int i = 0; i < R; i++) asm volatile("" : "+f"(d[i]) :: "memory");
}
template <int R> __device__ __forceinline__ void fence_regs(uint32_t (&d)[R]) {
    #pragma unroll
    for (int i = 0; i < R; i++) asm volatile("" : "+r"(d[i]) :: "memory");
}
__device__ __forceinline__ void quad_transpose(uint32_t (&r)[4], int t) {
    uint32_t s0 = (t & 1) ? r[0] : r[1], s1 = (t & 1) ? r[2] : r[3];
    s0 = __shfl_xor_sync(0xffffffffu, s0, 1); s1 = __shfl_xor_sync(0xffffffffu, s1, 1);
    if (t & 1) { r[0] = s0; r[2] = s1; } else { r[1] = s0; r[3] = s1; }
    s0 = (t & 2) ? r[0] : r[2]; s1 = (t & 2) ? r[1] : r[3];
    s0 = __shfl_xor_sync(0xffffffffu, s0, 2); s1 = __shfl_xor_sync(0xffffffffu, s1, 2);
    if (t & 2) { r[0] = s0; r[1] = s1; } else { r[2] = s0; r[3] = s1; }
}
template <int R> __device__ __forceinline__ void pack32(const float (&a)[R], int b0, int rr, float scale, uint32_t (&r)[4]) {
    #pragma unroll
    for (int b = 0; b < 4; b++) r[b] = pack_bf16(a[4 * (b0 + b) + 2 * rr] * scale, a[4 * (b0 + b) + 2 * rr + 1] * scale);
}
__device__ __forceinline__ float sumsq4(const uint32_t (&r)[4]) {
    float s = 0.f;
    #pragma unroll
    for (int b = 0; b < 4; b++) { float lo = bf_lo(r[b]), hi = bf_hi(r[b]); s = fmaf(lo, lo, s); s = fmaf(hi, hi, s); }
    s += __shfl_xor_sync(0xffffffffu, s, 1); s += __shfl_xor_sync(0xffffffffu, s, 2);
    return s;
}

__device__ __forceinline__ void wg_ss_n192_tb(float (&d)[96], uint64_t da, uint64_t db, int sd) {
    asm volatile("{\n.reg .pred p;\nsetp.ne.b32 p, %98, 0;\n"
        "wgmma.mma_async.sync.aligned.m64n192k16.f32.bf16.bf16 {"
        "%0, %1, %2, %3, %4, %5, %6, %7, %8, %9, %10, %11, %12, %13, %14, %15, "
        "%16, %17, %18, %19, %20, %21, %22, %23, %24, %25, %26, %27, %28, %29, %30, %31, "
        "%32, %33, %34, %35, %36, %37, %38, %39, %40, %41, %42, %43, %44, %45, %46, %47, "
        "%48, %49, %50, %51, %52, %53, %54, %55, %56, %57, %58, %59, %60, %61, %62, %63, "
        "%64, %65, %66, %67, %68, %69, %70, %71, %72, %73, %74, %75, %76, %77, %78, %79, "
        "%80, %81, %82, %83, %84, %85, %86, %87, %88, %89, %90, %91, %92, %93, %94, %95}, %96, %97, p, 1, 1, 0, 1;\n}\n"
        : "+f"(d[0]), "+f"(d[1]), "+f"(d[2]), "+f"(d[3]), "+f"(d[4]), "+f"(d[5]), "+f"(d[6]), "+f"(d[7]),
          "+f"(d[8]), "+f"(d[9]), "+f"(d[10]), "+f"(d[11]), "+f"(d[12]), "+f"(d[13]), "+f"(d[14]), "+f"(d[15]),
          "+f"(d[16]), "+f"(d[17]), "+f"(d[18]), "+f"(d[19]), "+f"(d[20]), "+f"(d[21]), "+f"(d[22]), "+f"(d[23]),
          "+f"(d[24]), "+f"(d[25]), "+f"(d[26]), "+f"(d[27]), "+f"(d[28]), "+f"(d[29]), "+f"(d[30]), "+f"(d[31]),
          "+f"(d[32]), "+f"(d[33]), "+f"(d[34]), "+f"(d[35]), "+f"(d[36]), "+f"(d[37]), "+f"(d[38]), "+f"(d[39]),
          "+f"(d[40]), "+f"(d[41]), "+f"(d[42]), "+f"(d[43]), "+f"(d[44]), "+f"(d[45]), "+f"(d[46]), "+f"(d[47]),
          "+f"(d[48]), "+f"(d[49]), "+f"(d[50]), "+f"(d[51]), "+f"(d[52]), "+f"(d[53]), "+f"(d[54]), "+f"(d[55]),
          "+f"(d[56]), "+f"(d[57]), "+f"(d[58]), "+f"(d[59]), "+f"(d[60]), "+f"(d[61]), "+f"(d[62]), "+f"(d[63]),
          "+f"(d[64]), "+f"(d[65]), "+f"(d[66]), "+f"(d[67]), "+f"(d[68]), "+f"(d[69]), "+f"(d[70]), "+f"(d[71]),
          "+f"(d[72]), "+f"(d[73]), "+f"(d[74]), "+f"(d[75]), "+f"(d[76]), "+f"(d[77]), "+f"(d[78]), "+f"(d[79]),
          "+f"(d[80]), "+f"(d[81]), "+f"(d[82]), "+f"(d[83]), "+f"(d[84]), "+f"(d[85]), "+f"(d[86]), "+f"(d[87]),
          "+f"(d[88]), "+f"(d[89]), "+f"(d[90]), "+f"(d[91]), "+f"(d[92]), "+f"(d[93]), "+f"(d[94]), "+f"(d[95])
        : "l"(da), "l"(db), "r"(sd));
}
__device__ __forceinline__ void wg_ss_n128_tb(float (&d)[64], uint64_t da, uint64_t db, int sd) {
    asm volatile("{\n.reg .pred p;\nsetp.ne.b32 p, %66, 0;\n"
        "wgmma.mma_async.sync.aligned.m64n128k16.f32.bf16.bf16 {"
        "%0, %1, %2, %3, %4, %5, %6, %7, %8, %9, %10, %11, %12, %13, %14, %15, "
        "%16, %17, %18, %19, %20, %21, %22, %23, %24, %25, %26, %27, %28, %29, %30, %31, "
        "%32, %33, %34, %35, %36, %37, %38, %39, %40, %41, %42, %43, %44, %45, %46, %47, "
        "%48, %49, %50, %51, %52, %53, %54, %55, %56, %57, %58, %59, %60, %61, %62, %63}, %64, %65, p, 1, 1, 0, 1;\n}\n"
        : "+f"(d[0]), "+f"(d[1]), "+f"(d[2]), "+f"(d[3]), "+f"(d[4]), "+f"(d[5]), "+f"(d[6]), "+f"(d[7]),
          "+f"(d[8]), "+f"(d[9]), "+f"(d[10]), "+f"(d[11]), "+f"(d[12]), "+f"(d[13]), "+f"(d[14]), "+f"(d[15]),
          "+f"(d[16]), "+f"(d[17]), "+f"(d[18]), "+f"(d[19]), "+f"(d[20]), "+f"(d[21]), "+f"(d[22]), "+f"(d[23]),
          "+f"(d[24]), "+f"(d[25]), "+f"(d[26]), "+f"(d[27]), "+f"(d[28]), "+f"(d[29]), "+f"(d[30]), "+f"(d[31]),
          "+f"(d[32]), "+f"(d[33]), "+f"(d[34]), "+f"(d[35]), "+f"(d[36]), "+f"(d[37]), "+f"(d[38]), "+f"(d[39]),
          "+f"(d[40]), "+f"(d[41]), "+f"(d[42]), "+f"(d[43]), "+f"(d[44]), "+f"(d[45]), "+f"(d[46]), "+f"(d[47]),
          "+f"(d[48]), "+f"(d[49]), "+f"(d[50]), "+f"(d[51]), "+f"(d[52]), "+f"(d[53]), "+f"(d[54]), "+f"(d[55]),
          "+f"(d[56]), "+f"(d[57]), "+f"(d[58]), "+f"(d[59]), "+f"(d[60]), "+f"(d[61]), "+f"(d[62]), "+f"(d[63])
        : "l"(da), "l"(db), "r"(sd));
}
__device__ __forceinline__ void wg_ss_n64(float (&d)[32], uint64_t da, uint64_t db, int sd) {
    asm volatile("{\n.reg .pred p;\nsetp.ne.b32 p, %34, 0;\n"
        "wgmma.mma_async.sync.aligned.m64n64k16.f32.bf16.bf16 {"
        "%0, %1, %2, %3, %4, %5, %6, %7, %8, %9, %10, %11, %12, %13, %14, %15, "
        "%16, %17, %18, %19, %20, %21, %22, %23, %24, %25, %26, %27, %28, %29, %30, %31}, %32, %33, p, 1, 1, 0, 0;\n}\n"
        : "+f"(d[0]), "+f"(d[1]), "+f"(d[2]), "+f"(d[3]), "+f"(d[4]), "+f"(d[5]), "+f"(d[6]), "+f"(d[7]),
          "+f"(d[8]), "+f"(d[9]), "+f"(d[10]), "+f"(d[11]), "+f"(d[12]), "+f"(d[13]), "+f"(d[14]), "+f"(d[15]),
          "+f"(d[16]), "+f"(d[17]), "+f"(d[18]), "+f"(d[19]), "+f"(d[20]), "+f"(d[21]), "+f"(d[22]), "+f"(d[23]),
          "+f"(d[24]), "+f"(d[25]), "+f"(d[26]), "+f"(d[27]), "+f"(d[28]), "+f"(d[29]), "+f"(d[30]), "+f"(d[31])
        : "l"(da), "l"(db), "r"(sd));
}
__device__ __forceinline__ void wg_rs_n40(float (&d)[20], uint32_t a0, uint32_t a1, uint32_t a2, uint32_t a3, uint64_t db, int sd) {
    asm volatile("{\n.reg .pred p;\nsetp.ne.b32 p, %25, 0;\n"
        "wgmma.mma_async.sync.aligned.m64n40k16.f32.bf16.bf16 {"
        "%0, %1, %2, %3, %4, %5, %6, %7, %8, %9, %10, %11, %12, %13, %14, %15, "
        "%16, %17, %18, %19}, {%20, %21, %22, %23}, %24, p, 1, 1, 0;\n}\n"
        : "+f"(d[0]), "+f"(d[1]), "+f"(d[2]), "+f"(d[3]), "+f"(d[4]), "+f"(d[5]), "+f"(d[6]), "+f"(d[7]),
          "+f"(d[8]), "+f"(d[9]), "+f"(d[10]), "+f"(d[11]), "+f"(d[12]), "+f"(d[13]), "+f"(d[14]), "+f"(d[15]),
          "+f"(d[16]), "+f"(d[17]), "+f"(d[18]), "+f"(d[19])
        : "r"(a0), "r"(a1), "r"(a2), "r"(a3), "l"(db), "r"(sd));
}
__device__ __forceinline__ void wg_rs_n32(float (&d)[16], uint32_t a0, uint32_t a1, uint32_t a2, uint32_t a3, uint64_t db, int sd) {
    asm volatile("{\n.reg .pred p;\nsetp.ne.b32 p, %21, 0;\n"
        "wgmma.mma_async.sync.aligned.m64n32k16.f32.bf16.bf16 {"
        "%0, %1, %2, %3, %4, %5, %6, %7, %8, %9, %10, %11, %12, %13, %14, %15}, {%16, %17, %18, %19}, %20, p, 1, 1, 0;\n}\n"
        : "+f"(d[0]), "+f"(d[1]), "+f"(d[2]), "+f"(d[3]), "+f"(d[4]), "+f"(d[5]), "+f"(d[6]), "+f"(d[7]),
          "+f"(d[8]), "+f"(d[9]), "+f"(d[10]), "+f"(d[11]), "+f"(d[12]), "+f"(d[13]), "+f"(d[14]), "+f"(d[15])
        : "r"(a0), "r"(a1), "r"(a2), "r"(a3), "l"(db), "r"(sd));
}
__device__ __forceinline__ void wg_ss_n40_ta(float (&d)[20], uint64_t da, uint64_t db, int sd) {
    asm volatile("{\n.reg .pred p;\nsetp.ne.b32 p, %22, 0;\n"
        "wgmma.mma_async.sync.aligned.m64n40k16.f32.bf16.bf16 {"
        "%0, %1, %2, %3, %4, %5, %6, %7, %8, %9, %10, %11, %12, %13, %14, %15, "
        "%16, %17, %18, %19}, %20, %21, p, 1, 1, 1, 0;\n}\n"
        : "+f"(d[0]), "+f"(d[1]), "+f"(d[2]), "+f"(d[3]), "+f"(d[4]), "+f"(d[5]), "+f"(d[6]), "+f"(d[7]),
          "+f"(d[8]), "+f"(d[9]), "+f"(d[10]), "+f"(d[11]), "+f"(d[12]), "+f"(d[13]), "+f"(d[14]), "+f"(d[15]),
          "+f"(d[16]), "+f"(d[17]), "+f"(d[18]), "+f"(d[19])
        : "l"(da), "l"(db), "r"(sd));
}

__device__ __forceinline__ float acc_sumsq(const float (&a)[96], int b0, int rr) {
    float s = 0.f;
    #pragma unroll
    for (int b = 0; b < 4; b++) { s = fmaf(a[4 * (b0 + b) + 2 * rr], a[4 * (b0 + b) + 2 * rr], s); s = fmaf(a[4 * (b0 + b) + 2 * rr + 1], a[4 * (b0 + b) + 2 * rr + 1], s); }
    return s;
}
__device__ __forceinline__ float quad_norms(const float (&a)[96], int X, int t) {
    const float p0 = acc_sumsq(a, X * 8, 0), p1 = acc_sumsq(a, X * 8, 1), p2 = acc_sumsq(a, X * 8 + 4, 0), p3 = acc_sumsq(a, X * 8 + 4, 1);
    const float k0 = (t & 1) ? p1 : p0, s0 = (t & 1) ? p0 : p1, k1 = (t & 1) ? p3 : p2, s1 = (t & 1) ? p2 : p3;
    const float u0 = k0 + __shfl_xor_sync(0xffffffffu, s0, 1), u1 = k1 + __shfl_xor_sync(0xffffffffu, s1, 1);
    return ((t & 2) ? u1 : u0) + __shfl_xor_sync(0xffffffffu, (t & 2) ? u0 : u1, 2);
}
__device__ __forceinline__ void publish_norm(float v, int X, uint8_t* sp, int lane) {
    v = fmaxf(v, __shfl_xor_sync(0xffffffffu, v, 1));
    v = fmaxf(v, __shfl_xor_sync(0xffffffffu, v, 4)); v = fmaxf(v, __shfl_xor_sync(0xffffffffu, v, 8)); v = fmaxf(v, __shfl_xor_sync(0xffffffffu, v, 16));
    if ((lane & ~2) == 0) atomicMax((unsigned int*)(sp + NORM_OFF) + X * 2 + (lane >> 1), __float_as_uint(v * (X == 0 ? 1.02f * 0.0650428f : 1.02f)));
}
template <int X>
__device__ __forceinline__ void p1_store_rows(const float (&a)[96], int m, int wg, int w4, int lane, uint32_t sb) {
    const float QS = 0.17677669529663687f * 1.4426950408889634f;
    const int mat = lane >> 3, i = lane & 7;
    #pragma unroll
    for (int hh = 0; hh < 2; hh++) {
        uint32_t vl[4], vh[4];
        pack32(a, X * 8 + hh * 4, 0, X == 0 ? QS : 1.f, vl);
        pack32(a, X * 8 + hh * 4, 1, X == 0 ? QS : 1.f, vh);
        const int row = m * 64 + w4 * 16 + (mat & 1) * 8 + i;
        const uint32_t base = (X == 0 ? sb + Q_OFF + hh * 16384 + wg * 8192 : sb + KV_OFF + (hh * 2 + wg) * KV_STAGE) + row * 64;
        #pragma unroll
        for (int bp = 0; bp < 2; bp++)
            stsm4(base + (((2 * bp + (mat >> 1)) ^ ((row >> 1) & 3)) << 4), vl[2 * bp], vh[2 * bp], vl[2 * bp + 1], vh[2 * bp + 1]);
    }
}
__device__ __forceinline__ void p1_store_vt(const float (&a)[96], int m, int wg, int w4, int lane, uint32_t sb) {
    const int mat = lane >> 3, i = lane & 7;
    #pragma unroll
    for (int hh = 0; hh < 2; hh++) {
        uint32_t vl[4], vh[4];
        pack32(a, 16 + hh * 4, 0, 1.f, vl);
        pack32(a, 16 + hh * 4, 1, 1.f, vh);
        const uint32_t base = sb + KV_OFF + (hh * 2 + wg) * KV_STAGE + 8192 + m * 5120;
        #pragma unroll
        for (int bp = 0; bp < 2; bp++) {
            const int rowd = 8 * (2 * bp + (mat >> 1)) + i, chunk = 2 * w4 + (mat & 1);
            stsm4_t(base + rowd * 128 + ((chunk ^ i) << 4), vl[2 * bp], vh[2 * bp], vl[2 * bp + 1], vh[2 * bp + 1]);
        }
    }
}

__device__ __forceinline__ void phase1(uint32_t sb, uint8_t* sp, int wg, int w4, int lane) {
    const uint32_t bars = sb + BAR_OFF;
    const bool elect = (w4 == 0 && lane == 0);
    float a0[96], a1[96];
    #pragma unroll 1
    for (int ks = 0; ks < 16; ks++) {
        const int s = ks % R1_N;
        mbar_wait(bars + (B_FULL1 + s) * 8, (ks / R1_N) & 1);
        const uint32_t st = sb + s * R1_STAGE;
        const uint64_t da = D_K128 | desc_lo(st + wg * 16384);
        const uint64_t db = desc_hi(8192, 1024, 1) | desc_lo(st + R1_A);
        wg_fence();
        #pragma unroll
        for (int k = 0; k < 4; k++) {
            wg_ss_n192_tb(a0, da + k * 2, db + k * 128, (ks > 0 || k > 0) ? 1 : 0);
            wg_ss_n192_tb(a1, da + 512 + k * 2, db + k * 128, (ks > 0 || k > 0) ? 1 : 0);
        }
        wg_commit();
        wg_wait<0>();
        mbar_arrive_if(bars + (B_EMPTY1 + s) * 8, elect);
    }
    fence_regs(a0); fence_regs(a1);
    bar_sync(3, 256);
    const int tid = wg * 128 + w4 * 32 + lane;
    if (tid == 0) mbar_arrive(bars + B_R1FREE * 8);
    const int t = lane & 3;
    p1_store_rows<1>(a0, 0, wg, w4, lane, sb); p1_store_vt(a0, 0, wg, w4, lane, sb);
    p1_store_rows<1>(a1, 1, wg, w4, lane, sb); p1_store_vt(a1, 1, wg, w4, lane, sb);
    fence_async_smem();
    publish_norm(fmaxf(quad_norms(a0, 1, t), quad_norms(a1, 1, t)), 1, sp, lane);
    publish_norm(fmaxf(quad_norms(a0, 2, t), quad_norms(a1, 2, t)), 2, sp, lane);
    bar_sync(3, 256);
    if (tid == 0) mbar_arrive(bars + B_KVSTAGED * 8);
    p1_store_rows<0>(a0, 0, wg, w4, lane, sb);
    p1_store_rows<0>(a1, 1, wg, w4, lane, sb);
    fence_async_smem();
    publish_norm(fmaxf(quad_norms(a0, 0, t), quad_norms(a1, 0, t)), 0, sp, lane);
    bar_sync(3, 256);
    if (tid == 0) mbar_arrive(bars + B_P1DONE * 8);
}

__device__ __forceinline__ float exp2_fma(float x) {
    const float MAGIC = 12582912.f;
    const float t = __fadd_rn(x, MAGIC);
    const float f = __fadd_rn(x, -__fadd_rn(t, -MAGIC));
    float p = fmaf(0.0013277939287945628f, f, 0.009675757959485054f);
    p = fmaf(p, f, 0.05550709739327431f);
    p = fmaf(p, f, 0.24022114276885986f);
    p = fmaf(p, f, 0.6931469440460205f);
    p = fmaf(p, f, 1.0000001192092896f);
    return __uint_as_float(__float_as_uint(p) + (__float_as_uint(t) << 23));
}
__device__ __forceinline__ void exp_pack(const float (&s)[32], uint32_t (&p)[16]) {
    #pragma unroll
    for (int i = 0; i < 16; i++)
        p[i] = pack_bf16(ex2(s[2 * i]), (i == 11 || i == 15) ? exp2_fma(s[2 * i + 1]) : ex2(s[2 * i + 1]));
}
__device__ __forceinline__ void qk_issue(float (&s)[32], uint64_t dq, uint64_t dk) {
    wg_ss_n64(s, dq, dk, 0);
    wg_ss_n64(s, dq + 2, dk + 2, 1);
}
__device__ __forceinline__ void pv_issue(float (&o)[20], const uint32_t (&p)[16], uint64_t dv) {
    #pragma unroll
    for (int k = 0; k < 4; k++) wg_rs_n40(o, p[4 * k], p[4 * k + 1], p[4 * k + 2], p[4 * k + 3], dv + 2 * k, 1);
}
__device__ __forceinline__ void online_exp_pack(float (&s)[32], uint32_t (&p)[16], float (&o)[20], float (&mx)[2]) {
    #pragma unroll
    for (int rr = 0; rr < 2; rr++) {
        float m = mx[rr];
        #pragma unroll
        for (int b = 0; b < 8; b++) m = fmaxf(m, fmaxf(s[4 * b + 2 * rr], s[4 * b + 2 * rr + 1]));
        m = fmaxf(m, __shfl_xor_sync(0xffffffffu, m, 1)); m = fmaxf(m, __shfl_xor_sync(0xffffffffu, m, 2));
        const float sc = ex2(mx[rr] - m);
        mx[rr] = m;
        #pragma unroll
        for (int b = 0; b < 5; b++) { o[4 * b + 2 * rr] *= sc; o[4 * b + 2 * rr + 1] *= sc; }
        #pragma unroll
        for (int b = 0; b < 8; b++) p[2 * b + rr] = pack_bf16(ex2(s[4 * b + 2 * rr] - m), ex2(s[4 * b + 2 * rr + 1] - m));
    }
}
__device__ __forceinline__ void attn_stage(const float (&o)[20], uint32_t base, int w4, int lane) {
    uint32_t vl[4], vh[4];
    pack32(o, 0, 0, 1.f / __shfl_sync(0xffffffffu, o[16], lane & ~3), vl);
    pack32(o, 0, 1, 1.f / __shfl_sync(0xffffffffu, o[18], lane & ~3), vh);
    const int mat = lane >> 3, row = w4 * 16 + (mat & 1) * 8 + (lane & 7);
    #pragma unroll
    for (int bp = 0; bp < 2; bp++)
        stsm4(base + row * 64 + (((2 * bp + (mat >> 1)) ^ ((row >> 1) & 3)) << 4), vl[2 * bp], vh[2 * bp], vl[2 * bp + 1], vh[2 * bp + 1]);
}

__device__ __forceinline__ bool scores_bounded(float nq, float nk, float nv) {
    return (nq * nk <= 3600.f) && (nv <= 1e24f) && (nq <= 1e18f) && (nk <= 1e18f);
}
template <int NST, int S0>
__device__ __forceinline__ void attn_body(uint32_t bars, uint32_t par, int s0r, bool elect, uint64_t dqa, uint64_t dqb, uint64_t dkb, uint64_t dvb,
                                          float (&sa)[32], float (&sc)[32], uint32_t (&pa)[16], uint32_t (&pb)[16], float (&oa)[20], float (&ob)[20]) {
    const int s0 = S0 >= 0 ? S0 : s0r;
    #define SLOT(u) (S0 >= 0 ? ((S0 + (u)) & 3) : s0 + (u))
    #define PAR(u) (S0 >= 0 ? par ^ (((S0 + (u)) >> 2) & 1) : par)
    mbar_wait(bars + (B_KVFULL + SLOT(0)) * 8, par);
    wg_fence();
    qk_issue(sa, dqa, dkb + SLOT(0) * (KV_STAGE >> 4)); wg_commit();
    qk_issue(sc, dqb, dkb + SLOT(0) * (KV_STAGE >> 4)); wg_commit();
    #pragma unroll
    for (int q = 0; q < 2 * NST; q++) {
        const int u = q >> 1, half = q & 1, qn = q + 1;
        const uint64_t dv = dvb + SLOT(u) * (KV_STAGE >> 4) + half * (5120 >> 4);
        const uint64_t dkn = dkb + SLOT(qn >> 1) * (KV_STAGE >> 4) + (qn & 1) * (4096 >> 4);
        wg_wait<1>();
        fence_regs(sa);
        exp_pack(sa, pa);
        if (half == 1 && qn < 2 * NST) mbar_wait(bars + (B_KVFULL + SLOT(u + 1)) * 8, PAR(u + 1));
        fence_regs(pa);
        wg_fence();
        pv_issue(oa, pa, dv);
        if (qn < 2 * NST) qk_issue(sa, dqa, dkn);
        wg_commit();
        wg_wait<1>();
        fence_regs(sc);
        if (half == 0 && u > 0) mbar_arrive_if(bars + (B_KVEMPTY + SLOT(u - 1)) * 8, elect);
        exp_pack(sc, pb);
        fence_regs(pb);
        wg_fence();
        pv_issue(ob, pb, dv);
        if (qn < 2 * NST) qk_issue(sc, dqb, dkn);
        wg_commit();
    }
    wg_wait<0>();
    fence_regs(oa); fence_regs(ob);
    mbar_arrive_if(bars + (B_KVEMPTY + SLOT(NST - 1)) * 8, elect);
    #undef SLOT
    #undef PAR
}

__device__ __forceinline__ void attention(uint32_t sb, uint8_t* sp, int wg, int w4, int lane) {
    const uint32_t bars = sb + BAR_OFF;
    const bool elect = (w4 == 0 && lane == 0);
    const volatile float* nloc = (const volatile float*)(sp + NORM_OFF);
    #pragma unroll 1
    for (int task = 0; task < 2; task++) {
        bool fast = true;
        if (task == 0) fast = scores_bounded(nloc[0], nloc[2], nloc[4]);
        const uint64_t dqa = D_K64 | desc_lo(sb + Q_OFF + task * 16384 + wg * 8192), dqb = dqa + 256;
        float oa[20], ob[20], sa[32], sc[32];
        uint32_t pa[16], pb[16];
        #pragma unroll
        for (int i = 0; i < 20; i++) { oa[i] = 0.f; ob[i] = 0.f; }
        fence_regs(oa); fence_regs(ob);
        const uint64_t dkb = D_K64 | desc_lo(sb + KV_OFF), dvb = D_K128 | desc_lo(sb + KV_OFF + 8192);
        int body = 0;
        #pragma unroll 1
        for (; body < 8; body++) {
            if (body == (task == 0 ? 1 : 0)) {
                mbar_wait(bars + B_NORMOK * 8, 0);
                fast = fast && ((*((const volatile unsigned int*)(sp + NORM_OFF) + 8) >> task) & 1u);
            }
            if (!fast) break;
            const uint32_t par = (task * 4 + (body >> 1)) & 1;
            if (task == 0 && body < 2) attn_body<2, -1>(bars, par, body * 2, elect, dqa, dqb, dkb, dvb, sa, sc, pa, pb, oa, ob);
            else { attn_body<4, 0>(bars, par, 0, elect, dqa, dqb, dkb, dvb, sa, sc, pa, pb, oa, ob); body++; }
        }
        if (body < 8) {
            const float m0 = body > 0 ? 0.f : -INFINITY;
            float ma[2] = {m0, m0}, mb[2] = {m0, m0};
            #pragma unroll 1
            for (int q = body * 4; q < 32; q++) {
                const int u = (q >> 1) & 3, half = q & 1;
                const uint32_t par = (task * 4 + (q >> 3)) & 1;
                if (half == 0) mbar_wait(bars + (B_KVFULL + u) * 8, par);
                const uint64_t dk = dkb + u * (KV_STAGE >> 4) + half * (4096 >> 4);
                const uint64_t dv = dvb + u * (KV_STAGE >> 4) + half * (5120 >> 4);
                wg_fence();
                qk_issue(sa, dqa, dk);
                qk_issue(sc, dqb, dk);
                wg_commit();
                wg_wait<0>();
                fence_regs(sa); fence_regs(sc);
                online_exp_pack(sa, pa, oa, ma);
                online_exp_pack(sc, pb, ob, mb);
                fence_regs(pa); fence_regs(pb); fence_regs(oa); fence_regs(ob);
                wg_fence();
                pv_issue(oa, pa, dv);
                pv_issue(ob, pb, dv);
                wg_commit();
                wg_wait<0>();
                fence_regs(oa); fence_regs(ob);
                if (half == 1) mbar_arrive_if(bars + (B_KVEMPTY + u) * 8, elect);
            }
        }
        attn_stage(oa, sb + Q_OFF + task * 16384 + wg * 8192, w4, lane);
        attn_stage(ob, sb + Q_OFF + task * 16384 + wg * 8192 + 4096, w4, lane);
        fence_async_smem();
        __syncwarp();
        mbar_arrive_if(bars + (B_ODONE + wg) * 8, lane == 0);
    }
}

__device__ __forceinline__ void phase3(uint32_t sb, int wg, int w4, int lane, int c, const Params& P) {
    const uint32_t bars = sb + BAR_OFF;
    const bool elect = (w4 == 0 && lane == 0);
    float a0[64], a1[64];
    #pragma unroll 1
    for (int ks = 0; ks < 16; ks++) {
        const int s = ks & 3;
        mbar_wait(bars + (B_FULL3 + s) * 8, (ks >> 2) & 1);
        const uint32_t st = sb + s * R3_STAGE;
        const uint64_t db = desc_hi(8192, 1024, 1) | desc_lo(st + R3_A);
        const uint64_t da = D_K128 | desc_lo(st + wg * 8192);
        wg_fence();
        #pragma unroll
        for (int k = 0; k < 4; k++) {
            wg_ss_n128_tb(a0, da + k * 2, db + k * 128, (ks > 0 || k > 0) ? 1 : 0);
            wg_ss_n128_tb(a1, da + k * 2, db + 1024 + k * 128, (ks > 0 || k > 0) ? 1 : 0);
        }
        wg_commit();
        wg_wait<0>();
        mbar_arrive_if(bars + (B_EMPTY3 + s) * 8, elect);
    }
    fence_regs(a0); fence_regs(a1);
    const int br = c >> 6, rb = c & 15, cb = (c >> 4) & 3;
    bar_sync(3, 256);
    const uint32_t stg = sb + wg * 32768;
    const int mat = lane >> 3, row = w4 * 16 + (mat & 1) * 8 + (lane & 7);
    #pragma unroll
    for (int g = 0; g < 4; g++) {
        #pragma unroll
        for (int bp = 0; bp < 4; bp++) {
            const int b = (g & 1) * 8 + 2 * bp;
            const uint32_t ad = stg + g * 8192 + row * 128 + (((2 * bp + (mat >> 1)) ^ (lane & 7)) << 4);
            if (g < 2) stsm4(ad, pack_bf16(a0[4 * b], a0[4 * b + 1]), pack_bf16(a0[4 * b + 2], a0[4 * b + 3]), pack_bf16(a0[4 * b + 4], a0[4 * b + 5]), pack_bf16(a0[4 * b + 6], a0[4 * b + 7]));
            else stsm4(ad, pack_bf16(a1[4 * b], a1[4 * b + 1]), pack_bf16(a1[4 * b + 2], a1[4 * b + 3]), pack_bf16(a1[4 * b + 4], a1[4 * b + 5]), pack_bf16(a1[4 * b + 6], a1[4 * b + 7]));
        }
        fence_async_smem();
        bar_sync(1 + wg, 128);
        if (elect) { tma2d_store(&P.out, stg + g * 8192, br * 1024 + cb * 256 + g * 64, rb * 128 + wg * 64); bulk_commit(); }
    }
    if (elect) bulk_wait_all();
}

__device__ __forceinline__ uint32_t hmax2(uint32_t a, uint32_t b) { uint32_t r; asm("max.bf16x2 %0, %1, %2;" : "=r"(r) : "r"(a), "r"(b)); return r; }
__device__ __forceinline__ uint32_t hmin2(uint32_t a, uint32_t b) { uint32_t r; asm("min.bf16x2 %0, %1, %2;" : "=r"(r) : "r"(a), "r"(b)); return r; }
__device__ __forceinline__ float rcp(float x) { float y; asm("rcp.approx.ftz.f32 %0, %1;" : "=f"(y) : "f"(x)); return y; }
__device__ __forceinline__ void feature_map(const float (&px)[16], uint32_t (&F)[8][2]) {
    const float L2E = 1.4426950408889634f;
    #pragma unroll
    for (int rr = 0; rr < 2; rr++) {
        uint32_t pk[4];
        #pragma unroll
        for (int b = 0; b < 4; b++) pk[b] = pack_bf16(px[4 * b + 2 * rr], px[4 * b + 2 * rr + 1]);
        const uint32_t m2 = hmax2(hmax2(pk[0], pk[1]), hmax2(pk[2], pk[3]));
        const uint32_t n2 = hmin2(hmin2(pk[0], pk[1]), hmin2(pk[2], pk[3])) ^ 0x80008000u;
        uint32_t t = hmax2(__byte_perm(m2, n2, 0x5410), __byte_perm(m2, n2, 0x7632));
        t = hmax2(t, __shfl_xor_sync(0xffffffffu, t, 1));
        t = hmax2(t, __shfl_xor_sync(0xffffffffu, t, 2));
        const float nmx = -bf_lo(t) * L2E, pmn = -bf_hi(t) * L2E;
        float x[8];
        #pragma unroll
        for (int b = 0; b < 4; b++) { x[2 * b] = bf_lo(pk[b]); x[2 * b + 1] = bf_hi(pk[b]); }
        float ep[8], en[8], sp = 0.f, sn = 0.f;
        #pragma unroll
        for (int i = 0; i < 8; i++) {
            ep[i] = ex2(fmaf(x[i], L2E, nmx)); en[i] = ex2(fmaf(x[i], -L2E, pmn));
            sp += ep[i]; sn += en[i];
        }
        sp += __shfl_xor_sync(0xffffffffu, sp, 1); sn += __shfl_xor_sync(0xffffffffu, sn, 1);
        sp += __shfl_xor_sync(0xffffffffu, sp, 2); sn += __shfl_xor_sync(0xffffffffu, sn, 2);
        const float ip = rcp(sp), in = rcp(sn);
        #pragma unroll
        for (int b = 0; b < 4; b++) {
            F[b][rr] = pack_bf16(ep[2 * b] * ip, ep[2 * b + 1] * ip);
            F[4 + b][rr] = pack_bf16(en[2 * b] * in, en[2 * b + 1] * in);
        }
    }
}

__device__ __forceinline__ void a_epilogue(const float (&a)[96], uint32_t sb, int w4, int lane, int tile, int j) {
    uint32_t fk[8][2];
    const int mat = lane >> 3, i = lane & 7;
    const uint32_t scr = sb + SCR_OFF;
    {
        #pragma unroll
        for (int hh = 0; hh < 2; hh++) {
            uint32_t vl[4], vh[4];
            pack32(a, 16 + hh * 4, 0, 1.f, vl);
            pack32(a, 16 + hh * 4, 1, 1.f, vh);
            #pragma unroll
            for (int bp = 0; bp < 2; bp++) {
                const int rowd = 8 * (2 * bp + (mat >> 1)) + i, chunk = 2 * w4 + (mat & 1);
                stsm4_t(scr + 16384 + hh * 5120 + rowd * 128 + ((chunk ^ i) << 4), vl[2 * bp], vh[2 * bp], vl[2 * bp + 1], vh[2 * bp + 1]);
            }
        }
        #pragma unroll
        for (int kk = 0; kk < 4; kk++)
            g_qfrag[(size_t)(tile * 4 + kk) * 128 + w4 * 32 + lane] = make_uint4(pack_bf16(a[8 * kk], a[8 * kk + 1]), pack_bf16(a[8 * kk + 2], a[8 * kk + 3]),
                                                                                  pack_bf16(a[8 * kk + 4], a[8 * kk + 5]), pack_bf16(a[8 * kk + 6], a[8 * kk + 7]));
        #pragma unroll
        for (int b = 0; b < 8; b++) {
            fk[b][0] = pack_bf16(a[4 * (8 + b)], a[4 * (8 + b) + 1]); fk[b][1] = pack_bf16(a[4 * (8 + b) + 2], a[4 * (8 + b) + 3]);
        }
    }
    const uint64_t dw0 = D_K64 | desc_lo(sb + WPHI_OFF), dw1 = dw0 + 128;
    {
        float px0[16], px1[16];
        #pragma unroll
        for (int b = 0; b < 8; b++) fence_regs(fk[b]);
        wg_fence();
        wg_rs_n32(px0, fk[0][0], fk[0][1], fk[1][0], fk[1][1], dw0, 0);
        wg_rs_n32(px0, fk[2][0], fk[2][1], fk[3][0], fk[3][1], dw0 + 2, 1);
        wg_rs_n32(px1, fk[4][0], fk[4][1], fk[5][0], fk[5][1], dw1, 0);
        wg_rs_n32(px1, fk[6][0], fk[6][1], fk[7][0], fk[7][1], dw1 + 2, 1);
        wg_commit();
        wg_wait<0>();
        fence_regs(px0); fence_regs(px1);
        uint32_t F0[8][2], F1[8][2];
        feature_map(px0, F0);
        feature_map(px1, F1);
        #pragma unroll
        for (int bp = 0; bp < 4; bp++) {
            const int srow = w4 * 16 + (mat & 1) * 8 + i, chunk = 2 * bp + (mat >> 1);
            const uint32_t ad = scr + srow * 128 + ((chunk ^ i) << 4);
            stsm4(ad, F0[2 * bp][0], F0[2 * bp][1], F0[2 * bp + 1][0], F0[2 * bp + 1][1]);
            stsm4(ad + 8192, F1[2 * bp][0], F1[2 * bp][1], F1[2 * bp + 1][0], F1[2 * bp + 1][1]);
        }
    }
    fence_async_smem();
    bar_sync(4, 128);
    float kv0[20], kv1[20];
    {
        const uint64_t dA0 = desc_hi(8192, 1024, 1) | desc_lo(scr), dA1 = dA0 + 512;
        const uint64_t dB0 = D_K128 | desc_lo(scr + 16384), dB1 = dB0 + 320;
        wg_fence();
        #pragma unroll
        for (int k = 0; k < 4; k++) wg_ss_n40_ta(kv0, dA0 + k * 128, dB0 + k * 2, k > 0 ? 1 : 0);
        #pragma unroll
        for (int k = 0; k < 4; k++) wg_ss_n40_ta(kv1, dA1 + k * 128, dB1 + k * 2, k > 0 ? 1 : 0);
        wg_commit();
        wg_wait<0>();
        fence_regs(kv0); fence_regs(kv1);
    }
    #pragma unroll
    for (int hh = 0; hh < 2; hh++) {
        float* dst = g_kv + (size_t)((2 * j + hh) * 64 + w4 * 16 + (lane >> 2)) * 40 + (lane & 3) * 2;
        #pragma unroll
        for (int b = 0; b < 5; b++) {
            if (b < 4 || (lane & 3) == 0) {
                #pragma unroll
                for (int rr = 0; rr < 2; rr++) {
                    const float v0 = hh == 0 ? kv0[4 * b + 2 * rr] : kv1[4 * b + 2 * rr], v1 = hh == 0 ? kv0[4 * b + 2 * rr + 1] : kv1[4 * b + 2 * rr + 1];
                    asm volatile("red.global.add.v2.f32 [%0], {%1, %2};" :: "l"(dst + rr * 8 * 40 + b * 8), "f"(v0), "f"(v1) : "memory");
                }
            }
        }
    }
}

__device__ __forceinline__ void phi_q_issue(uint32_t (&fq)[16], uint64_t dw0, uint64_t dw1, float (&px0)[16], float (&px1)[16]) {
    wg_rs_n32(px0, fq[0], fq[1], fq[2], fq[3], dw0, 0);
    wg_rs_n32(px0, fq[4], fq[5], fq[6], fq[7], dw0 + 2, 1);
    wg_rs_n32(px1, fq[8], fq[9], fq[10], fq[11], dw1, 0);
    wg_rs_n32(px1, fq[12], fq[13], fq[14], fq[15], dw1 + 2, 1);
}
__device__ __forceinline__ void load_qfrag(uint32_t (&fq)[16], int tile, int tid) {
    #pragma unroll
    for (int q = 0; q < 4; q++) {
        const uint4 v = __ldcg(&g_qfrag[(size_t)(tile * 4 + q) * 128 + tid]);
        fq[4 * q] = v.x; fq[4 * q + 1] = v.y; fq[4 * q + 2] = v.z; fq[4 * q + 3] = v.w;
    }
}

__device__ __forceinline__ void a_branch(uint32_t sb, uint8_t* sp, int w4, int lane, int r, int j, unsigned int epoch, const Params& P) {
    const uint32_t bars = sb + BAR_OFF;
    const int tid = w4 * 32 + lane;
    const bool elect = (tid == 0);
    for (int i = tid; i < 2 * 256; i += 128) {
        const int hh = i >> 8, w = i & 255;
        *(uint32_t*)(sp + SCR_OFF + 16384 + hh * 5120 + 4096 + w * 4) = (w < 32) ? 0x3F803F80u : 0u;
    }
    #pragma unroll 1
    for (int i = 0; i < 4; i++) {
        float a[96];
        #pragma unroll
        for (int q = 0; q < 96; q++) a[q] = 0.f;
        fence_regs(a);
        const uint64_t da0 = D_K128 | desc_lo(sb + GX_OFF), db0 = desc_hi(4096, 1024, 1) | desc_lo(sb);
        #pragma unroll 1
        for (int ks = 0; ks < 32; ks += 8) {
            #pragma unroll
            for (int u = 0; u < 8; u++) {
                mbar_wait(bars + (B_GFULL + (u & 3)) * 8, (u >> 2) & 1);
                const uint64_t da = da0 + (((u >> 1) & 3) * GX_STAGE + (u & 1) * 64 >> 4), db = db0 + ((u & 3) * GW_STAGE >> 4);
                wg_fence();
                wg_ss_n192_tb(a, da, db, 1);
                wg_ss_n192_tb(a, da + 2, db + 128, 1);
                wg_commit();
                wg_wait<1>();
                mbar_arrive_if(bars + (B_GEMPTY + ((u + 3) & 3)) * 8, elect && (u > 0 || ks > 0));
            }
        }
        wg_wait<0>();
        mbar_arrive_if(bars + (B_GEMPTY + 3) * 8, elect);
        fence_regs(a);
        if (i == 0) { if (elect) flag_wait(&g_cntB[j], 8 * (epoch + 1)); }
        bar_sync(4, 128);
        a_epilogue(a, sb, w4, lane, (r * 4 + i) * 16 + j, j);
    }
    bar_sync(4, 128);
    if (elect) mbar_arrive(bars + B_KVDONE * 8);
    const uint64_t dw0 = D_K64 | desc_lo(sb + WPHI_OFF), dw1 = dw0 + 128;
    uint32_t F0[8][2], F1[8][2], fq[16];
    {
        float px0[16], px1[16];
        load_qfrag(fq, (r * 4) * 16 + j, tid);
        fence_regs(fq);
        wg_fence();
        phi_q_issue(fq, dw0, dw1, px0, px1);
        wg_commit();
        wg_wait<0>();
        fence_regs(px0); fence_regs(px1);
        load_qfrag(fq, (r * 4 + 1) * 16 + j, tid);
        feature_map(px0, F0);
        feature_map(px1, F1);
    }
    if (elect) flag_wait(&g_cntA[j], 8 * (epoch + 1));
    bar_sync(4, 128);
    {
        const int hh = tid >> 6, fp = (tid >> 1) & 31, half = tid & 1, f = fp * 2;
        const float4* src0 = (const float4*)(g_kv + (size_t)((2 * j + hh) * 64 + f) * 40 + half * 20);
        float4 v0[5], v1[5];
        #pragma unroll
        for (int q = 0; q < 5; q++) { v0[q] = __ldcg(src0 + q); v1[q] = __ldcg(src0 + 10 + q); }
        #pragma unroll
        for (int q = 0; q < 5; q++) {
            const float e0[4] = {v0[q].x, v0[q].y, v0[q].z, v0[q].w}, e1[4] = {v1[q].x, v1[q].y, v1[q].z, v1[q].w};
            #pragma unroll
            for (int e = 0; e < 4; e++) {
                const int n = half * 20 + q * 4 + e;
                *(uint32_t*)(sp + SCR_OFF + hh * 5120 + n * 128 + (((f >> 3) ^ (n & 7)) << 4) + (f & 7) * 2) = n <= 32 ? pack_bf16(e0[e], e1[e]) : 0u;
            }
        }
    }
    fence_async_smem();
    bar_sync(4, 128);
    {
        const uint64_t dB0 = D_K128 | desc_lo(sb + SCR_OFF), dB1 = dB0 + 320;
        #pragma unroll 1
        for (int i = 0; i < 4; i++) {
            float o0[20], o1[20], px0[16], px1[16];
            #pragma unroll
            for (int b = 0; b < 8; b++) { fence_regs(F0[b]); fence_regs(F1[b]); }
            fence_regs(fq);
            wg_fence();
            #pragma unroll
            for (int kk = 0; kk < 4; kk++) wg_rs_n40(o0, F0[2 * kk][0], F0[2 * kk][1], F0[2 * kk + 1][0], F0[2 * kk + 1][1], dB0 + 2 * kk, kk > 0 ? 1 : 0);
            #pragma unroll
            for (int kk = 0; kk < 4; kk++) wg_rs_n40(o1, F1[2 * kk][0], F1[2 * kk][1], F1[2 * kk + 1][0], F1[2 * kk + 1][1], dB1 + 2 * kk, kk > 0 ? 1 : 0);
            phi_q_issue(fq, dw0, dw1, px0, px1);
            wg_commit();
            wg_wait<0>();
            fence_regs(o0); fence_regs(o1); fence_regs(px0); fence_regs(px1);
            load_qfrag(fq, (r * 4 + (i + 2 < 4 ? i + 2 : 3)) * 16 + j, tid);
            #pragma unroll
            for (int hh = 0; hh < 2; hh++) {
                uint32_t vl[4];
                #pragma unroll
                for (int rr = 0; rr < 2; rr++) {
                    float den = __shfl_sync(0xffffffffu, hh == 0 ? o0[16 + 2 * rr] : o1[16 + 2 * rr], lane & ~3);
                    den = bf_round(bf_round(den) + 1e-6f);
                    const float inv = rcp(den);
                    uint32_t v[4];
                    #pragma unroll
                    for (int b = 0; b < 4; b++) {
                        const uint32_t pk = hh == 0 ? pack_bf16(o0[4 * b + 2 * rr], o0[4 * b + 2 * rr + 1]) : pack_bf16(o1[4 * b + 2 * rr], o1[4 * b + 2 * rr + 1]);
                        v[b] = pack_bf16(bf_lo(pk) * inv, bf_hi(pk) * inv);
                    }
                    if (rr == 0) { vl[0] = v[0]; vl[1] = v[1]; vl[2] = v[2]; vl[3] = v[3]; }
                    else {
                        const int srow = (i & 1) * 64 + w4 * 16 + ((lane >> 3) & 1) * 8 + (lane & 7);
                        #pragma unroll
                        for (int bp = 0; bp < 2; bp++)
                            stsm4(sb + (i >> 1) * 16384 + srow * 128 + (((hh * 4 + 2 * bp + (lane >> 4)) ^ (lane & 7)) << 4), vl[2 * bp], v[2 * bp], vl[2 * bp + 1], v[2 * bp + 1]);
                    }
                }
            }
            if (i == 3) break;
            feature_map(px0, F0);
            feature_map(px1, F1);
        }
    }
    fence_async_smem();
    bar_sync(4, 128);
    if (elect) {
        for (int u = 0; u < 2; u++) tma2d_store(&P.o, sb + u * 16384, j * 64, r * 256 + u * 128);
        bulk_commit();
        bulk_wait_all();
        mbar_arrive(bars + B_ADONE * 8);
        asm volatile("fence.proxy.async.global;" ::: "memory");
        flag_signal_relaxed(&g_cntOA[r]);
    }
}

__global__ void __launch_bounds__(512, 1) fused_kernel(const __grid_constant__ Params P) {
    extern __shared__ uint8_t smem_raw[];
    const uint32_t sb = (smem_u32(smem_raw) + 1023) & ~1023u;
    uint8_t* sp = smem_raw + (sb - smem_u32(smem_raw));
    const uint32_t bars = sb + BAR_OFF;
    const int c = blockIdx.x, r = c & 7, j = c >> 3;
    if (threadIdx.x == 384) {
        for (int s = 0; s < R1_N; s++) { mbar_init(bars + (B_FULL1 + s) * 8, 1); mbar_init(bars + (B_EMPTY1 + s) * 8, 2); }
        asm volatile("fence.mbarrier_init.release.cluster;" ::: "memory");
        fence_async_smem();
        for (int ks = 0; ks < R1_N; ks++) {
            const uint32_t st = sb + ks * R1_STAGE, fb = bars + (B_FULL1 + ks) * 8;
            mbar_expect_tx(fb, R1_STAGE);
            tma2d(st, &P.xB, ks * 64, r * 256, fb);
            tma3d(st + R1_A, &P.wB, j * 64, ks * 64, 0, fb);
        }
    }
    if (threadIdx.x < 120) {
        const int i = threadIdx.x;
        const char* src = i < 48 ? (const char*)P.pxB + (size_t)(r * 256 + j * 16 + i / 3) * 2048 + (i % 3) * 128
                                 : (const char*)P.pwB + (size_t)(r * 24 + (i - 48) / 3) * 6144 + ((i - 48) % 3) * 2048 + j * 128;
        asm volatile("prefetch.global.L2 [%0];" :: "l"(src));
    }
    const int warp = __shfl_sync(0xffffffffu, (int)(threadIdx.x >> 5), 0), lane = threadIdx.x & 31, wg = warp >> 2, w4 = warp & 3;
    const unsigned int epoch = __ldcg(&g_epoch[c]);
    if (threadIdx.x == 416) { prefetch_map(&P.xA); prefetch_map(&P.wA); prefetch_map(&P.o); prefetch_map(&P.oS); prefetch_map(&P.woA); prefetch_map(&P.woB); prefetch_map(&P.out); }
    if (threadIdx.x == 0) {
        for (int s = 0; s < KV_N; s++) { mbar_init(bars + (B_KVFULL + s) * 8, 1); mbar_init(bars + (B_KVEMPTY + s) * 8, 2); }
        for (int s = 0; s < G_N; s++) { mbar_init(bars + (B_GFULL + s) * 8, 1); mbar_init(bars + (B_GEMPTY + s) * 8, 1); }
        for (int q = 0; q < 6; q++) *((unsigned int*)(sp + NORM_OFF) + q) = 0u;
    }
    if (threadIdx.x == 32) {
        for (int s = 0; s < R3_N; s++) { mbar_init(bars + (B_FULL3 + s) * 8, 1); mbar_init(bars + (B_EMPTY3 + s) * 8, 2); }
        mbar_init(bars + B_R1FREE * 8, 1); mbar_init(bars + B_P1DONE * 8, 1); mbar_init(bars + B_P2DONE * 8, 2); mbar_init(bars + B_ADONE * 8, 1);
        mbar_init(bars + B_NORMOK * 8, 1); mbar_init(bars + B_ODONE * 8, 4); mbar_init(bars + (B_ODONE + 1) * 8, 4);
        mbar_init(bars + B_KVDONE * 8, 1); mbar_init(bars + B_KVSTAGED * 8, 2);
    }
    if (threadIdx.x == 0 || threadIdx.x == 32) asm volatile("fence.mbarrier_init.release.cluster;" ::: "memory");
    __syncthreads();

    if (wg == 3) {
        reg_dealloc<24>();
        if (warp == 12) {
            for (int ks = R1_N; ks < 16; ks++) {
                const int s = ks % R1_N;
                mbar_wait(bars + (B_EMPTY1 + s) * 8, ((ks / R1_N) - 1) & 1);
                const uint32_t st = sb + s * R1_STAGE, fb = bars + (B_FULL1 + s) * 8;
                if (elect_one()) {
                    mbar_expect_tx(fb, R1_STAGE);
                    tma2d(st, &P.xB, ks * 64, r * 256, fb);
                    tma3d(st + R1_A, &P.wB, j * 64, ks * 64, 0, fb);
                    if (ks >= 3 && ks < 13) {
                        const int q = ks - 3;
                        const char* src = q < 6 ? (const char*)P.pwA + (size_t)c * 49152 + q * 8192 : (const char*)P.pxA + (size_t)c * 32768 + (q - 6) * 8192;
                        asm volatile("cp.async.bulk.prefetch.L2.global [%0], %1;" :: "l"(src), "r"(8192u) : "memory");
                    }
                }
                __syncwarp();
            }
            mbar_wait_long(bars + B_KVSTAGED * 8, 0);
            if (lane == 0) {
                for (int q = 0; q < 4; q++) {
                    const int hh = q >> 1, w = q & 1;
                    const uint32_t st = sb + KV_OFF + q * KV_STAGE;
                    bulk_store(&g_kimg[(size_t)((2 * j + hh) * 16 + 2 * r + w) * 512], st, 8192);
                    bulk_store(&g_vimg[(size_t)((2 * j + hh) * 32 + (2 * r + w) * 2) * 256], st + 8192, 4096);
                    bulk_store(&g_vimg[(size_t)((2 * j + hh) * 32 + (2 * r + w) * 2 + 1) * 256], st + 8192 + 5120, 4096);
                    if (q & 1) bulk_commit();
                }
                {
                    float chk = 0.f;
                    for (int q = 0; q < 4; q++) {
                        float* dst = &g_norm[((q >> 1) * NH + 2 * j + (q & 1)) * 8 + r];
                        asm volatile("st.relaxed.gpu.global.f32 [%0], %1;" :: "l"(dst), "f"(__uint_as_float(*((volatile unsigned int*)(sp + NORM_OFF) + 2 + q))) : "memory");
                        float v; asm volatile("ld.relaxed.gpu.global.f32 %0, [%1];" : "=f"(v) : "l"(dst) : "memory");
                        chk += v;
                    }
                    asm volatile("" :: "f"(chk) : "memory");
                }
                asm volatile("cp.async.bulk.wait_group 1;" ::: "memory");
                asm volatile("fence.proxy.async.global;" ::: "memory");
                flag_signal_relaxed(&g_cntB[j]);
                asm volatile("cp.async.bulk.wait_group.read 0;" ::: "memory");
                flag_wait(&g_cntB[j], 8 * (epoch + 1));
                asm volatile("fence.proxy.async.global;" ::: "memory");
            }
            __syncwarp();
            for (int g = 2; g < 32; g++) {
                const int s = g & 3, h = 2 * j + (g >> 4), t = (2 * r + g) & 15;
                if (g >= KV_N) mbar_wait_long(bars + (B_KVEMPTY + s) * 8, ((g >> 2) - 1) & 1);
                const uint32_t st = sb + KV_OFF + s * KV_STAGE, fb = bars + (B_KVFULL + s) * 8;
                if (elect_one()) {
                    mbar_expect_tx(fb, 16384);
                    bulk_load(st, &g_kimg[(size_t)(h * 16 + t) * 512], 8192, fb);
                    bulk_load(st + 8192, &g_vimg[(size_t)(h * 32 + 2 * t) * 256], 4096, fb);
                    bulk_load(st + 8192 + 5120, &g_vimg[(size_t)(h * 32 + 2 * t + 1) * 256], 4096, fb);
                    if (g >= 8 && g < 12) {
                        const char* src = (g < 10 ? (const char*)P.pwoA : (const char*)P.pwoB) + (size_t)c * 16384 + (g & 1) * 8192;
                        asm volatile("cp.async.bulk.prefetch.L2.global [%0], %1;" :: "l"(src), "r"(8192u) : "memory");
                    }
                }
                __syncwarp();
                if (g == 3) {
                    if (lane == 0) {
                        bulk_wait_all();
                        asm volatile("fence.proxy.async.global;" ::: "memory");
                        flag_signal_relaxed(&g_cntB[16 + j]);
                    }
                    __syncwarp();
                }
                if (g == 15) {
                    if (lane == 0) { flag_wait(&g_cntB[16 + j], 8 * (epoch + 1)); asm volatile("fence.proxy.async.global;" ::: "memory"); }
                    __syncwarp();
                }
            }
            const int br = c >> 6, rb = c & 15, cb = (c >> 4) & 3;
            for (int ks = 0; ks < 16; ks++) {
                const int s = ks & 3;
                if (ks == 0) {
                    mbar_wait_long(bars + B_ADONE * 8, 0);
                    if (lane == 0) {
                        if (br == 0) flag_wait(&g_cntOA[rb >> 1], 16 * (epoch + 1)); else flag_wait(&g_cntOB[rb >> 1], 32 * (epoch + 1));
                        asm volatile("fence.proxy.async.global;" ::: "memory");
                    }
                    __syncwarp();
                }
                if (ks == 1) mbar_wait(bars + (B_KVEMPTY + 0) * 8, 1);
                if (ks == 2) { mbar_wait(bars + (B_KVEMPTY + 1) * 8, 1); mbar_wait(bars + (B_KVEMPTY + 2) * 8, 1); mbar_wait(bars + (B_KVEMPTY + 3) * 8, 1); }
                if (ks == 3) mbar_wait(bars + B_P2DONE * 8, 0);
                if (ks == 8 && br == 1) {
                    if (lane == 0) { flag_wait(&g_cntOB[8 + (rb >> 1)], 32 * (epoch + 1)); asm volatile("fence.proxy.async.global;" ::: "memory"); }
                    __syncwarp();
                }
                if (ks >= R3_N) mbar_wait(bars + (B_EMPTY3 + s) * 8, ((ks >> 2) - 1) & 1);
                const uint32_t st = sb + s * R3_STAGE, fb = bars + (B_FULL3 + s) * 8;
                if (elect_one()) {
                    mbar_expect_tx(fb, R3_STAGE);
                    tma2d(st, &P.o, ks * 64, br * SEQ + rb * 128, fb);
                    if (br == 0) tma3d(st + R3_A, &P.woA, 0, ks * 64, cb * 4, fb);
                    else tma5d(st + R3_A, &P.woB, 0, 0, ks >> 3, 2 * (ks & 7), cb * 4, fb);
                }
                __syncwarp();
            }
        } else if (warp == 13) {
            mbar_wait_long(bars + B_R1FREE * 8, 0);
            for (int it = 0; it < 128; it++) {
                const int s = it & 3, i = it >> 5, ks = it & 31;
                if (it >= G_N) mbar_wait(bars + (B_GEMPTY + s) * 8, ((it >> 2) - 1) & 1);
                const uint32_t fb = bars + (B_GFULL + s) * 8;
                if (elect_one()) {
                    mbar_expect_tx(fb, (it & 1) ? GW_STAGE : GW_STAGE + GX_STAGE);
                    if (!(it & 1)) tma2d(sb + GX_OFF + ((it >> 1) & 3) * GX_STAGE, &P.xA, ks * 32, r * 256 + i * 64, fb);
                    tma3d(sb + s * GW_STAGE, &P.wA, j * 64, ks * 32, 0, fb);
                }
                __syncwarp();
            }
        } else if (warp == 15) {
            if (lane == 0) {
                for (int q = 0; q < 4; q++) {
                    const int w = q & 1, task = q >> 1;
                    mbar_wait_long(bars + (B_ODONE + w) * 8, task);
                    tma2d_store(&P.oS, sb + Q_OFF + task * 16384 + w * 8192, task * 512 + j * 32, SEQ + r * 256 + w * 128);
                    bulk_commit();
                    bulk_wait_all();
                    if (task == 1) mbar_arrive(bars + B_P2DONE * 8);
                    asm volatile("fence.proxy.async.global;" ::: "memory");
                    flag_signal_relaxed(&g_cntOB[task * 8 + r]);
                }
            }
        } else {
            mbar_wait_long(bars + B_R1FREE * 8, 0);
            for (int i = lane; i < KV_N * 2 * 64; i += 32) {
                const int w = i & 63;
                *(uint4*)(sp + KV_OFF + (i >> 7) * KV_STAGE + 8192 + ((i >> 6) & 1) * 5120 + 4096 + w * 16) =
                    w < 8 ? make_uint4(0x3F803F80u, 0x3F803F80u, 0x3F803F80u, 0x3F803F80u) : make_uint4(0u, 0u, 0u, 0u);
            }
            fence_async_smem();
            __syncwarp();
            if (lane == 0) {
                mbar_wait(bars + B_KVSTAGED * 8, 0);
                mbar_arrive(bars + (B_KVFULL + 0) * 8);
                mbar_arrive(bars + (B_KVFULL + 1) * 8);
                flag_wait(&g_cntB[j], 8 * (epoch + 1));
            }
            __syncwarp();
            {
                float v = __ldcg(&g_norm[((lane >> 4) * NH + 2 * j + ((lane >> 3) & 1)) * 8 + (lane & 7)]);
                v = fmaxf(v, __shfl_xor_sync(0xffffffffu, v, 1)); v = fmaxf(v, __shfl_xor_sync(0xffffffffu, v, 2)); v = fmaxf(v, __shfl_xor_sync(0xffffffffu, v, 4));
                const float nk0 = __shfl_sync(0xffffffffu, v, 0), nk1 = __shfl_sync(0xffffffffu, v, 8), nv0 = __shfl_sync(0xffffffffu, v, 16), nv1 = __shfl_sync(0xffffffffu, v, 24);
                mbar_wait(bars + B_P1DONE * 8, 0);
                if (lane == 0) {
                    const volatile float* nloc = (const volatile float*)(sp + NORM_OFF);
                    *((volatile unsigned int*)(sp + NORM_OFF) + 8) = (scores_bounded(nloc[0], nk0, nv0) ? 1u : 0u) | (scores_bounded(nloc[1], nk1, nv1) ? 2u : 0u);
                    mbar_arrive(bars + B_NORMOK * 8);
                    mbar_wait_long(bars + B_KVDONE * 8, 0);
                    flag_signal(&g_cntA[j]);
                }
            }
        }
    } else if (wg == 2) {
        reg_dealloc<24>();
        for (int i = threadIdx.x & 127; i < 2048; i += 128) {
            const int hh = i >> 10, d = (i >> 5) & 31, f = i & 31;
            *(__nv_bfloat16*)(sp + WPHI_OFF + hh * 2048 + f * 64 + (((d >> 3) ^ ((f >> 1) & 3)) << 4) + (d & 7) * 2) = P.wphi[(size_t)(2 * j + hh) * 1024 + d * 32 + f];
        }
        fence_async_smem();
        if (r == 0) {
            float4* z = (float4*)(g_kv + (size_t)2 * j * 64 * 40);
            for (int i = threadIdx.x & 127; i < 2 * 64 * 40 / 4; i += 128) z[i] = make_float4(0.f, 0.f, 0.f, 0.f);
            __threadfence();
        }
        bar_sync(4, 128);
        if ((threadIdx.x & 127) == 0) mbar_arrive(bars + B_KVSTAGED * 8);
        mbar_wait_long(bars + B_P1DONE * 8, 0);
        reg_alloc<152>();
        a_branch(sb, sp, w4, lane, r, j, epoch, P);
    } else {
        reg_alloc<232>();
        phase1(sb, sp, wg, w4, lane);
        reg_dealloc<168>();
        attention(sb, sp, wg, w4, lane);
        phase3(sb, wg, w4, lane, c, P);
        if (threadIdx.x == 0) g_epoch[c] = epoch + 1;
    }
}

typedef CUresult (*EncodeFn)(CUtensorMap*, CUtensorMapDataType, cuuint32_t, void*, const cuuint64_t*, const cuuint64_t*, const cuuint32_t*,
                             const cuuint32_t*, CUtensorMapInterleave, CUtensorMapSwizzle, CUtensorMapL2promotion, CUtensorMapFloatOOBfill);
static void make_map(EncodeFn enc, CUtensorMap* m, const void* ptr, uint64_t inner, uint64_t outer, uint32_t box_inner, uint32_t box_outer, CUtensorMapSwizzle swz) {
    cuuint64_t gd[2] = {inner, outer}; cuuint64_t gs[1] = {inner * 2}; cuuint32_t bd[2] = {box_inner, box_outer}; cuuint32_t es[2] = {1, 1};
    enc(m, CU_TENSOR_MAP_DATA_TYPE_BFLOAT16, 2, const_cast<void*>(ptr), gd, gs, bd, es, CU_TENSOR_MAP_INTERLEAVE_NONE, swz,
        CU_TENSOR_MAP_L2_PROMOTION_L2_128B, CU_TENSOR_MAP_FLOAT_OOB_FILL_NONE);
}

struct Dims { uint64_t v[5]; };
static void make_map_nd(EncodeFn enc, CUtensorMap* m, const void* ptr, int rank, Dims dims, Dims strides, Dims box) {
    cuuint64_t gd[5], gs[5]; cuuint32_t bd[5], es[5];
    for (int i = 0; i < 5; i++) { gd[i] = dims.v[i]; gs[i] = strides.v[i]; bd[i] = (cuuint32_t)box.v[i]; es[i] = 1; }
    enc(m, CU_TENSOR_MAP_DATA_TYPE_BFLOAT16, rank, const_cast<void*>(ptr), gd, gs, bd, es, CU_TENSOR_MAP_INTERLEAVE_NONE, CU_TENSOR_MAP_SWIZZLE_128B,
        CU_TENSOR_MAP_L2_PROMOTION_L2_128B, CU_TENSOR_MAP_FLOAT_OOB_FILL_NONE);
}

}

extern "C" void kernel_launch(void* const* d_in, const int* in_sizes, int n_in, void* d_out, int out_size) {
    using namespace hk;
    (void)in_sizes; (void)n_in; (void)out_size;
    const __nv_bfloat16* A_x = (const __nv_bfloat16*)d_in[0];
    const __nv_bfloat16* A_wqkv = (const __nv_bfloat16*)d_in[1];
    const __nv_bfloat16* A_wphi = (const __nv_bfloat16*)d_in[2];
    const __nv_bfloat16* A_wo = (const __nv_bfloat16*)d_in[3];
    const __nv_bfloat16* B_x = (const __nv_bfloat16*)d_in[4];
    const __nv_bfloat16* B_wqkv = (const __nv_bfloat16*)d_in[5];
    const __nv_bfloat16* B_wo = (const __nv_bfloat16*)d_in[6];
    static EncodeFn enc = nullptr;
    static void* p_o = nullptr;
    if (!enc) {
        void* fn = nullptr; cudaDriverEntryPointQueryResult qr;
        cudaGetDriverEntryPoint("cuTensorMapEncodeTiled", &fn, cudaEnableDefault, &qr);
        enc = (EncodeFn)fn;
        cudaGetSymbolAddress(&p_o, g_o);
        cudaFuncSetAttribute(fused_kernel, cudaFuncAttributeMaxDynamicSharedMemorySize, SMEM_BYTES);
    }
    Params P;
    const CUtensorMapSwizzle S128 = CU_TENSOR_MAP_SWIZZLE_128B, S64 = CU_TENSOR_MAP_SWIZZLE_64B;
    make_map(enc, &P.xB, B_x, DM, SEQ, 64, 256, S128);
    make_map_nd(enc, &P.wB, B_wqkv, 3, {DM, DM, 3}, {3 * DM * 2, DM * 2}, {64, 64, 3});
    make_map(enc, &P.xA, A_x, DM, SEQ, 64, 64, S128);
    make_map_nd(enc, &P.wA, A_wqkv, 3, {DM, DM, 3}, {3 * DM * 2, DM * 2}, {64, 32, 3});

    make_map(enc, &P.o, p_o, DM, 2 * SEQ, 64, 128, S128);
    make_map(enc, &P.oS, p_o, DM, 2 * SEQ, 32, 128, S64);
    make_map_nd(enc, &P.woA, A_wo, 3, {64, DM, 16}, {DM * 2, 128}, {64, 64, 4});
    make_map_nd(enc, &P.woB, B_wo, 5, {64, 32, 2, 16, 16}, {DM * 2, 32 * DM * 2, 64 * DM * 2, 128}, {64, 32, 1, 2, 4});

    P.pxB = B_x; P.pwB = B_wqkv; P.pxA = A_x; P.pwA = A_wqkv; P.pwoA = A_wo; P.pwoB = B_wo; P.wphi = A_wphi;
    make_map(enc, &P.out, d_out, 2 * DM, SEQ, 64, 64, S128);
    fused_kernel<<<128, 512, SMEM_BYTES, cudaStreamPerThread>>>(P);
}
```

```cpp
#include <cuda_runtime.h>
#include <cuda_bf16.h>
#include <cuda.h>
#include <stdint.h>

namespace hk {

constexpr int SEQ = 2048, DM = 1024, NH = 32;

__device__ uint4 g_kimg[NH * 16 * 512];
__device__ uint4 g_vimg[NH * 32 * 256];
__device__ __nv_bfloat16 g_o[2 * SEQ * DM];
__device__ uint4 g_qfrag[512 * 4 * 128];
__device__ float g_kv[NH * 64 * 40];
__device__ float g_norm[2 * NH * 8];
__device__ unsigned int g_cntB[32], g_cntA[16], g_cntOA[8], g_cntOB[16];
__device__ unsigned int g_epoch[128];

struct Params {
    CUtensorMap xB, wB, xA, wA, o, oS, woA, woB, out;
    const __nv_bfloat16 *pxB, *pwB, *pxA, *pwA, *pwoA, *pwoB, *wphi;
};

constexpr int R1_A = 256 * 64 * 2, R1_B = 192 * 64 * 2, R1_STAGE = R1_A + R1_B, R1_N = 3;
constexpr int GW_STAGE = 12288, G_N = 4, GX_OFF = G_N * GW_STAGE, GX_STAGE = 8192;
constexpr int KV_OFF = GX_OFF + 4 * GX_STAGE, KV_STAGE = 18432, KV_N = 4;
constexpr int Q_OFF = KV_OFF + KV_N * KV_STAGE;
constexpr int SCR_OFF = Q_OFF + 32768;
constexpr int WPHI_OFF = SCR_OFF + 26624;
constexpr int BAR_OFF = WPHI_OFF + 4096;
constexpr int R3_A = 128 * 64 * 2, R3_STAGE = R3_A + 256 * 64 * 2, R3_N = 4;
constexpr int SMEM_BYTES = BAR_OFF + 1024 + 1024;
static_assert(R3_N * R3_STAGE <= WPHI_OFF, "ring3");
static_assert(SMEM_BYTES <= 232448, "smem");
constexpr int B_FULL1 = 0, B_EMPTY1 = 3, B_KVFULL = 6, B_KVEMPTY = 10, B_GFULL = 14, B_GEMPTY = 18, B_FULL3 = 22, B_EMPTY3 = 26,
              B_R1FREE = 30, B_P1DONE = 31, B_P2DONE = 32, B_NORMOK = 33, B_ODONE = 34, B_KVDONE = 36, B_ADONE = 37, B_KVSTAGED = 38;
constexpr int NORM_OFF = BAR_OFF + 512;

__device__ __forceinline__ uint32_t smem_u32(const void* p) { return (uint32_t)__cvta_generic_to_shared(p); }
__device__ __forceinline__ void mbar_init(uint32_t bar, uint32_t cnt) { asm volatile("mbarrier.init.shared::cta.b64 [%0], %1;" :: "r"(bar), "r"(cnt) : "memory"); }
__device__ __forceinline__ void mbar_expect_tx(uint32_t bar, uint32_t bytes) { asm volatile("mbarrier.arrive.expect_tx.shared::cta.b64 _, [%0], %1;" :: "r"(bar), "r"(bytes) : "memory"); }
__device__ __forceinline__ void mbar_arrive(uint32_t bar) { asm volatile("mbarrier.arrive.shared::cta.b64 _, [%0];" :: "r"(bar) : "memory"); }
__device__ __forceinline__ void mbar_arrive_if(uint32_t bar, bool pred) {
    asm volatile("{\n.reg .pred p;\nsetp.ne.u32 p, %1, 0;\n@p mbarrier.arrive.shared::cta.b64 _, [%0];\n}\n" :: "r"(bar), "r"((uint32_t)pred) : "memory");
}
__device__ __forceinline__ void mbar_wait(uint32_t bar, uint32_t parity) {
    asm volatile("{\n.reg .pred p;\n.reg .u32 c;\nmov.u32 c, 0;\nLAB_WAIT:\nmbarrier.try_wait.parity.shared::cta.b64 p, [%0], %1;\n@p bra LAB_DONE;\n"
                 "add.u32 c, c, 1;\nsetp.lt.u32 p, c, 4194304;\n@p bra LAB_WAIT;\ntrap;\nLAB_DONE:\n}\n" :: "r"(bar), "r"(parity) : "memory");
}
__device__ __forceinline__ void mbar_wait_long(uint32_t bar, uint32_t parity) {
    asm volatile("{\n.reg .pred p;\n.reg .u32 c;\nmov.u32 c, 0;\nLAB_WAIT:\nmbarrier.try_wait.parity.shared::cta.b64 p, [%0], %1, 100000;\n@p bra LAB_DONE;\n"
                 "add.u32 c, c, 1;\nsetp.lt.u32 p, c, 262144;\n@p bra LAB_WAIT;\ntrap;\nLAB_DONE:\n}\n" :: "r"(bar), "r"(parity) : "memory");
}
__device__ __forceinline__ void flag_wait(const unsigned int* cnt, unsigned int target) {
    asm volatile("{\n.reg .pred p;\n.reg .u32 c, v;\nmov.u32 c, 0;\nLAB_WAIT:\nld.acquire.gpu.global.u32 v, [%0];\nsub.u32 v, v, %1;\nsetp.ge.s32 p, v, 0;\n@p bra LAB_DONE;\n"
                 "nanosleep.u32 64;\nadd.u32 c, c, 1;\nsetp.lt.u32 p, c, 4194304;\n@p bra LAB_WAIT;\ntrap;\nLAB_DONE:\n}\n" :: "l"(cnt), "r"(target) : "memory");
}
__device__ __forceinline__ void flag_signal(unsigned int* cnt) {
    asm volatile("red.release.gpu.global.add.u32 [%0], 1;" :: "l"(cnt) : "memory");
}
__device__ __forceinline__ void flag_signal_relaxed(unsigned int* cnt) {
    asm volatile("red.relaxed.gpu.global.add.u32 [%0], 1;" :: "l"(cnt) : "memory");
}
__device__ __forceinline__ void tma2d(uint32_t dst, const CUtensorMap* m, int c0, int c1, uint32_t bar) {
    asm volatile("cp.async.bulk.tensor.2d.shared::cluster.global.mbarrier::complete_tx::bytes [%0], [%1, {%3, %4}], [%2];"
                 :: "r"(dst), "l"(m), "r"(bar), "r"(c0), "r"(c1) : "memory");
}
__device__ __forceinline__ void tma3d(uint32_t dst, const CUtensorMap* m, int c0, int c1, int c2, uint32_t bar) {
    asm volatile("cp.async.bulk.tensor.3d.shared::cluster.global.mbarrier::complete_tx::bytes [%0], [%1, {%3, %4, %5}], [%2];"
                 :: "r"(dst), "l"(m), "r"(bar), "r"(c0), "r"(c1), "r"(c2) : "memory");
}
__device__ __forceinline__ void tma5d(uint32_t dst, const CUtensorMap* m, int c0, int c1, int c2, int c3, int c4, uint32_t bar) {
    asm volatile("cp.async.bulk.tensor.5d.shared::cluster.global.mbarrier::complete_tx::bytes [%0], [%1, {%3, %4, %5, %6, %7}], [%2];"
                 :: "r"(dst), "l"(m), "r"(bar), "r"(c0), "r"(c1), "r"(c2), "r"(c3), "r"(c4) : "memory");
}
__device__ __forceinline__ bool elect_one() {
    uint32_t p;
    asm volatile("{\n.reg .pred P;\nelect.sync _|P, 0xffffffff;\nselp.u32 %0, 1, 0, P;\n}\n" : "=r"(p));
    return p != 0;
}
__device__ __forceinline__ void prefetch_map(const CUtensorMap* m) { asm volatile("prefetch.tensormap [%0];" :: "l"(m) : "memory"); }
__device__ __forceinline__ void tma2d_store(const CUtensorMap* m, uint32_t src, int c0, int c1) {
    asm volatile("cp.async.bulk.tensor.2d.global.shared::cta.bulk_group [%0, {%2, %3}], [%1];" :: "l"(m), "r"(src), "r"(c0), "r"(c1) : "memory");
}
__device__ __forceinline__ void bulk_load(uint32_t dst, const void* src, uint32_t bytes, uint32_t bar) {
    asm volatile("cp.async.bulk.shared::cluster.global.mbarrier::complete_tx::bytes [%0], [%1], %2, [%3];" :: "r"(dst), "l"(src), "r"(bytes), "r"(bar) : "memory");
}
__device__ __forceinline__ void bulk_store(void* dst, uint32_t src, uint32_t bytes) {
    asm volatile("cp.async.bulk.global.shared::cta.bulk_group [%0], [%1], %2;" :: "l"(dst), "r"(src), "r"(bytes) : "memory");
}
__device__ __forceinline__ void bulk_commit() { asm volatile("cp.async.bulk.commit_group;" ::: "memory"); }
__device__ __forceinline__ void bulk_wait_all() { asm volatile("cp.async.bulk.wait_group 0;" ::: "memory"); }
__device__ __forceinline__ void fence_async_smem() { asm volatile("fence.proxy.async.shared::cta;" ::: "memory"); }
__device__ __forceinline__ void wg_fence() { asm volatile("wgmma.fence.sync.aligned;" ::: "memory"); }
__device__ __forceinline__ void wg_commit() { asm volatile("wgmma.commit_group.sync.aligned;" ::: "memory"); }
template <int N> __device__ __forceinline__ void wg_wait() { asm volatile("wgmma.wait_group.sync.aligned %0;" :: "n"(N) : "memory"); }
__device__ __forceinline__ void bar_sync(int id, int n) { asm volatile("bar.sync %0, %1;" :: "r"(id), "r"(n) : "memory"); }
template <int N> __device__ __forceinline__ void reg_alloc() { asm volatile("setmaxnreg.inc.sync.aligned.u32 %0;" :: "n"(N)); }
template <int N> __device__ __forceinline__ void reg_dealloc() { asm volatile("setmaxnreg.dec.sync.aligned.u32 %0;" :: "n"(N)); }
__device__ __forceinline__ void stsm4(uint32_t addr, uint32_t r0, uint32_t r1, uint32_t r2, uint32_t r3) {
    asm volatile("stmatrix.sync.aligned.m8n8.x4.shared.b16 [%0], {%1, %2, %3, %4};" :: "r"(addr), "r"(r0), "r"(r1), "r"(r2), "r"(r3) : "memory");
}
__device__ __forceinline__ void stsm4_t(uint32_t addr, uint32_t r0, uint32_t r1, uint32_t r2, uint32_t r3) {
    asm volatile("stmatrix.sync.aligned.m8n8.x4.trans.shared.b16 [%0], {%1, %2, %3, %4};" :: "r"(addr), "r"(r0), "r"(r1), "r"(r2), "r"(r3) : "memory");
}
__host__ __device__ constexpr uint64_t desc_hi(uint32_t lbo, uint32_t sbo, int swz) {
    return ((uint64_t)((lbo & 0x3FFFF) >> 4) << 16) | ((uint64_t)((sbo & 0x3FFFF) >> 4) << 32) | ((uint64_t)swz << 62);
}
__device__ __forceinline__ uint64_t desc_lo(uint32_t addr) { return (uint64_t)((addr & 0x3FFFF) >> 4); }
constexpr uint64_t D_K128 = desc_hi(16, 1024, 1);
constexpr uint64_t D_K64 = desc_hi(16, 512, 2);
__device__ __forceinline__ uint32_t pack_bf16(float lo, float hi) {
    uint32_t r; asm("cvt.rn.bf16x2.f32 %0, %1, %2;" : "=r"(r) : "f"(hi), "f"(lo)); return r;
}
__device__ __forceinline__ float bf_lo(uint32_t r) { return __uint_as_float(r << 16); }
__device__ __forceinline__ float bf_hi(uint32_t r) { return __uint_as_float(r & 0xFFFF0000u); }
__device__ __forceinline__ float bf_round(float x) { return __bfloat162float(__float2bfloat16_rn(x)); }
__device__ __forceinline__ float ex2(float x) { float y; asm("ex2.approx.ftz.f32 %0, %1;" : "=f"(y) : "f"(x)); return y; }
template <int R> __device__ __forceinline__ void fence_regs(float (&d)[R]) {
    #pragma unroll
    for (int i = 0; i < R; i++) asm volatile("" : "+f"(d[i]) :: "memory");
}
template <int R> __device__ __forceinline__ void fence_regs(uint32_t (&d)[R]) {
    #pragma unroll
    for (int i = 0; i < R; i++) asm volatile("" : "+r"(d[i]) :: "memory");
}
template <int R> __device__ __forceinline__ void pack32(const float (&a)[R], int b0, int rr, float scale, uint32_t (&r)[4]) {
    #pragma unroll
    for (int b = 0; b < 4; b++) r[b] = pack_bf16(a[4 * (b0 + b) + 2 * rr] * scale, a[4 * (b0 + b) + 2 * rr + 1] * scale);
}

__device__ __forceinline__ void wg_ss_n192_tb(float (&d)[96], uint64_t da, uint64_t db, int sd) {
    asm volatile("{\n.reg .pred p;\nsetp.ne.b32 p, %98, 0;\n"
        "wgmma.mma_async.sync.aligned.m64n192k16.f32.bf16.bf16 {"
        "%0, %1, %2, %3, %4, %5, %6, %7, %8, %9, %10, %11, %12, %13, %14, %15, "
        "%16, %17, %18, %19, %20, %21, %22, %23, %24, %25, %26, %27, %28, %29, %30, %31, "
        "%32, %33, %34, %35, %36, %37, %38, %39, %40, %41, %42, %43, %44, %45, %46, %47, "
        "%48, %49, %50, %51, %52, %53, %54, %55, %56, %57, %58, %59, %60, %61, %62, %63, "
        "%64, %65, %66, %67, %68, %69, %70, %71, %72, %73, %74, %75, %76, %77, %78, %79, "
        "%80, %81, %82, %83, %84, %85, %86, %87, %88, %89, %90, %91, %92, %93, %94, %95}, %96, %97, p, 1, 1, 0, 1;\n}\n"
        : "+f"(d[0]), "+f"(d[1]), "+f"(d[2]), "+f"(d[3]), "+f"(d[4]), "+f"(d[5]), "+f"(d[6]), "+f"(d[7]),
          "+f"(d[8]), "+f"(d[9]), "+f"(d[10]), "+f"(d[11]), "+f"(d[12]), "+f"(d[13]), "+f"(d[14]), "+f"(d[15]),
          "+f"(d[16]), "+f"(d[17]), "+f"(d[18]), "+f"(d[19]), "+f"(d[20]), "+f"(d[21]), "+f"(d[22]), "+f"(d[23]),
          "+f"(d[24]), "+f"(d[25]), "+f"(d[26]), "+f"(d[27]), "+f"(d[28]), "+f"(d[29]), "+f"(d[30]), "+f"(d[31]),
          "+f"(d[32]), "+f"(d[33]), "+f"(d[34]), "+f"(d[35]), "+f"(d[36]), "+f"(d[37]), "+f"(d[38]), "+f"(d[39]),
          "+f"(d[40]), "+f"(d[41]), "+f"(d[42]), "+f"(d[43]), "+f"(d[44]), "+f"(d[45]), "+f"(d[46]), "+f"(d[47]),
          "+f"(d[48]), "+f"(d[49]), "+f"(d[50]), "+f"(d[51]), "+f"(d[52]), "+f"(d[53]), "+f"(d[54]), "+f"(d[55]),
          "+f"(d[56]), "+f"(d[57]), "+f"(d[58]), "+f"(d[59]), "+f"(d[60]), "+f"(d[61]), "+f"(d[62]), "+f"(d[63]),
          "+f"(d[64]), "+f"(d[65]), "+f"(d[66]), "+f"(d[67]), "+f"(d[68]), "+f"(d[69]), "+f"(d[70]), "+f"(d[71]),
          "+f"(d[72]), "+f"(d[73]), "+f"(d[74]), "+f"(d[75]), "+f"(d[76]), "+f"(d[77]), "+f"(d[78]), "+f"(d[79]),
          "+f"(d[80]), "+f"(d[81]), "+f"(d[82]), "+f"(d[83]), "+f"(d[84]), "+f"(d[85]), "+f"(d[86]), "+f"(d[87]),
          "+f"(d[88]), "+f"(d[89]), "+f"(d[90]), "+f"(d[91]), "+f"(d[92]), "+f"(d[93]), "+f"(d[94]), "+f"(d[95])
        : "l"(da), "l"(db), "r"(sd));
}
__device__ __forceinline__ void wg_ss_n128_tb(float (&d)[64], uint64_t da, uint64_t db, int sd) {
    asm volatile("{\n.reg .pred p;\nsetp.ne.b32 p, %66, 0;\n"
        "wgmma.mma_async.sync.aligned.m64n128k16.f32.bf16.bf16 {"
        "%0, %1, %2, %3, %4, %5, %6, %7, %8, %9, %10, %11, %12, %13, %14, %15, "
        "%16, %17, %18, %19, %20, %21, %22, %23, %24, %25, %26, %27, %28, %29, %30, %31, "
        "%32, %33, %34, %35, %36, %37, %38, %39, %40, %41, %42, %43, %44, %45, %46, %47, "
        "%48, %49, %50, %51, %52, %53, %54, %55, %56, %57, %58, %59, %60, %61, %62, %63}, %64, %65, p, 1, 1, 0, 1;\n}\n"
        : "+f"(d[0]), "+f"(d[1]), "+f"(d[2]), "+f"(d[3]), "+f"(d[4]), "+f"(d[5]), "+f"(d[6]), "+f"(d[7]),
          "+f"(d[8]), "+f"(d[9]), "+f"(d[10]), "+f"(d[11]), "+f"(d[12]), "+f"(d[13]), "+f"(d[14]), "+f"(d[15]),
          "+f"(d[16]), "+f"(d[17]), "+f"(d[18]), "+f"(d[19]), "+f"(d[20]), "+f"(d[21]), "+f"(d[22]), "+f"(d[23]),
          "+f"(d[24]), "+f"(d[25]), "+f"(d[26]), "+f"(d[27]), "+f"(d[28]), "+f"(d[29]), "+f"(d[30]), "+f"(d[31]),
          "+f"(d[32]), "+f"(d[33]), "+f"(d[34]), "+f"(d[35]), "+f"(d[36]), "+f"(d[37]), "+f"(d[38]), "+f"(d[39]),
          "+f"(d[40]), "+f"(d[41]), "+f"(d[42]), "+f"(d[43]), "+f"(d[44]), "+f"(d[45]), "+f"(d[46]), "+f"(d[47]),
          "+f"(d[48]), "+f"(d[49]), "+f"(d[50]), "+f"(d[51]), "+f"(d[52]), "+f"(d[53]), "+f"(d[54]), "+f"(d[55]),
          "+f"(d[56]), "+f"(d[57]), "+f"(d[58]), "+f"(d[59]), "+f"(d[60]), "+f"(d[61]), "+f"(d[62]), "+f"(d[63])
        : "l"(da), "l"(db), "r"(sd));
}
__device__ __forceinline__ void wg_ss_n64(float (&d)[32], uint64_t da, uint64_t db, int sd) {
    asm volatile("{\n.reg .pred p;\nsetp.ne.b32 p, %34, 0;\n"
        "wgmma.mma_async.sync.aligned.m64n64k16.f32.bf16.bf16 {"
        "%0, %1, %2, %3, %4, %5, %6, %7, %8, %9, %10, %11, %12, %13, %14, %15, "
        "%16, %17, %18, %19, %20, %21, %22, %23, %24, %25, %26, %27, %28, %29, %30, %31}, %32, %33, p, 1, 1, 0, 0;\n}\n"
        : "+f"(d[0]), "+f"(d[1]), "+f"(d[2]), "+f"(d[3]), "+f"(d[4]), "+f"(d[5]), "+f"(d[6]), "+f"(d[7]),
          "+f"(d[8]), "+f"(d[9]), "+f"(d[10]), "+f"(d[11]), "+f"(d[12]), "+f"(d[13]), "+f"(d[14]), "+f"(d[15]),
          "+f"(d[16]), "+f"(d[17]), "+f"(d[18]), "+f"(d[19]), "+f"(d[20]), "+f"(d[21]), "+f"(d[22]), "+f"(d[23]),
          "+f"(d[24]), "+f"(d[25]), "+f"(d[26]), "+f"(d[27]), "+f"(d[28]), "+f"(d[29]), "+f"(d[30]), "+f"(d[31])
        : "l"(da), "l"(db), "r"(sd));
}
__device__ __forceinline__ void wg_rs_n40(float (&d)[20], uint32_t a0, uint32_t a1, uint32_t a2, uint32_t a3, uint64_t db, int sd) {
    asm volatile("{\n.reg .pred p;\nsetp.ne.b32 p, %25, 0;\n"
        "wgmma.mma_async.sync.aligned.m64n40k16.f32.bf16.bf16 {"
        "%0, %1, %2, %3, %4, %5, %6, %7, %8, %9, %10, %11, %12, %13, %14, %15, "
        "%16, %17, %18, %19}, {%20, %21, %22, %23}, %24, p, 1, 1, 0;\n}\n"
        : "+f"(d[0]), "+f"(d[1]), "+f"(d[2]), "+f"(d[3]), "+f"(d[4]), "+f"(d[5]), "+f"(d[6]), "+f"(d[7]),
          "+f"(d[8]), "+f"(d[9]), "+f"(d[10]), "+f"(d[11]), "+f"(d[12]), "+f"(d[13]), "+f"(d[14]), "+f"(d[15]),
          "+f"(d[16]), "+f"(d[17]), "+f"(d[18]), "+f"(d[19])
        : "r"(a0), "r"(a1), "r"(a2), "r"(a3), "l"(db), "r"(sd));
}
__device__ __forceinline__ void wg_rs_n32(float (&d)[16], uint32_t a0, uint32_t a1, uint32_t a2, uint32_t a3, uint64_t db, int sd) {
    asm volatile("{\n.reg .pred p;\nsetp.ne.b32 p, %21, 0;\n"
        "wgmma.mma_async.sync.aligned.m64n32k16.f32.bf16.bf16 {"
        "%0, %1, %2, %3, %4, %5, %6, %7, %8, %9, %10, %11, %12, %13, %14, %15}, {%16, %17, %18, %19}, %20, p, 1, 1, 0;\n}\n"
        : "+f"(d[0]), "+f"(d[1]), "+f"(d[2]), "+f"(d[3]), "+f"(d[4]), "+f"(d[5]), "+f"(d[6]), "+f"(d[7]),
          "+f"(d[8]), "+f"(d[9]), "+f"(d[10]), "+f"(d[11]), "+f"(d[12]), "+f"(d[13]), "+f"(d[14]), "+f"(d[15])
        : "r"(a0), "r"(a1), "r"(a2), "r"(a3), "l"(db), "r"(sd));
}
__device__ __forceinline__ void wg_ss_n40_ta(float (&d)[20], uint64_t da, uint64_t db, int sd) {
    asm volatile("{\n.reg .pred p;\nsetp.ne.b32 p, %22, 0;\n"
        "wgmma.mma_async.sync.aligned.m64n40k16.f32.bf16.bf16 {"
        "%0, %1, %2, %3, %4, %5, %6, %7, %8, %9, %10, %11, %12, %13, %14, %15, "
        "%16, %17, %18, %19}, %20, %21, p, 1, 1, 1, 0;\n}\n"
        : "+f"(d[0]), "+f"(d[1]), "+f"(d[2]), "+f"(d[3]), "+f"(d[4]), "+f"(d[5]), "+f"(d[6]), "+f"(d[7]),
          "+f"(d[8]), "+f"(d[9]), "+f"(d[10]), "+f"(d[11]), "+f"(d[12]), "+f"(d[13]), "+f"(d[14]), "+f"(d[15]),
          "+f"(d[16]), "+f"(d[17]), "+f"(d[18]), "+f"(d[19])
        : "l"(da), "l"(db), "r"(sd));
}

__device__ __forceinline__ float acc_sumsq(const float (&a)[96], int b0, int rr) {
    float s = 0.f;
    #pragma unroll
    for (int b = 0; b < 4; b++) { s = fmaf(a[4 * (b0 + b) + 2 * rr], a[4 * (b0 + b) + 2 * rr], s); s = fmaf(a[4 * (b0 + b) + 2 * rr + 1], a[4 * (b0 + b) + 2 * rr + 1], s); }
    return s;
}
__device__ __forceinline__ float quad_norms(const float (&a)[96], int X, int t) {
    const float p0 = acc_sumsq(a, X * 8, 0), p1 = acc_sumsq(a, X * 8, 1), p2 = acc_sumsq(a, X * 8 + 4, 0), p3 = acc_sumsq(a, X * 8 + 4, 1);
    const float k0 = (t & 1) ? p1 : p0, s0 = (t & 1) ? p0 : p1, k1 = (t & 1) ? p3 : p2, s1 = (t & 1) ? p2 : p3;
    const float u0 = k0 + __shfl_xor_sync(0xffffffffu, s0, 1), u1 = k1 + __shfl_xor_sync(0xffffffffu, s1, 1);
    return ((t & 2) ? u1 : u0) + __shfl_xor_sync(0xffffffffu, (t & 2) ? u0 : u1, 2);
}
__device__ __forceinline__ void publish_norm(float v, int X, uint8_t* sp, int lane) {
    v = fmaxf(v, __shfl_xor_sync(0xffffffffu, v, 1));
    v = fmaxf(v, __shfl_xor_sync(0xffffffffu, v, 4)); v = fmaxf(v, __shfl_xor_sync(0xffffffffu, v, 8)); v = fmaxf(v, __shfl_xor_sync(0xffffffffu, v, 16));
    if ((lane & ~2) == 0) atomicMax((unsigned int*)(sp + NORM_OFF) + X * 2 + (lane >> 1), __float_as_uint(v * (X == 0 ? 1.02f * 0.0650428f : 1.02f)));
}
template <int X>
__device__ __forceinline__ void p1_store_rows(const float (&a)[96], int m, int wg, int w4, int lane, uint32_t sb) {
    const float QS = 0.17677669529663687f * 1.4426950408889634f;
    const int mat = lane >> 3, i = lane & 7;
    #pragma unroll
    for (int hh = 0; hh < 2; hh++) {
        uint32_t vl[4], vh[4];
        pack32(a, X * 8 + hh * 4, 0, X == 0 ? QS : 1.f, vl);
        pack32(a, X * 8 + hh * 4, 1, X == 0 ? QS : 1.f, vh);
        const int row = m * 64 + w4 * 16 + (mat & 1) * 8 + i;
        const uint32_t base = (X == 0 ? sb + Q_OFF + hh * 16384 + wg * 8192 : sb + KV_OFF + (hh * 2 + wg) * KV_STAGE) + row * 64;
        #pragma unroll
        for (int bp = 0; bp < 2; bp++)
            stsm4(base + (((2 * bp + (mat >> 1)) ^ ((row >> 1) & 3)) << 4), vl[2 * bp], vh[2 * bp], vl[2 * bp + 1], vh[2 * bp + 1]);
    }
}
__device__ __forceinline__ void p1_store_vt(const float (&a)[96], int m, int wg, int w4, int lane, uint32_t sb) {
    const int mat = lane >> 3, i = lane & 7;
    #pragma unroll
    for (int hh = 0; hh < 2; hh++) {
        uint32_t vl[4], vh[4];
        pack32(a, 16 + hh * 4, 0, 1.f, vl);
        pack32(a, 16 + hh * 4, 1, 1.f, vh);
        const uint32_t base = sb + KV_OFF + (hh * 2 + wg) * KV_STAGE + 8192 + m * 5120;
        #pragma unroll
        for (int bp = 0; bp < 2; bp++) {
            const int rowd = 8 * (2 * bp + (mat >> 1)) + i, chunk = 2 * w4 + (mat & 1);
            stsm4_t(base + rowd * 128 + ((chunk ^ i) << 4), vl[2 * bp], vh[2 * bp], vl[2 * bp + 1], vh[2 * bp + 1]);
        }
    }
}

__device__ __forceinline__ void phase1(uint32_t sb, uint8_t* sp, int wg, int w4, int lane) {
    const uint32_t bars = sb + BAR_OFF;
    const bool elect = (w4 == 0 && lane == 0);
    float a0[96], a1[96];
    #pragma unroll 1
    for (int ks = 0; ks < 16; ks++) {
        const int s = ks % R1_N;
        mbar_wait(bars + (B_FULL1 + s) * 8, (ks / R1_N) & 1);
        const uint32_t st = sb + s * R1_STAGE;
        const uint64_t da = D_K128 | desc_lo(st + wg * 16384);
        const uint64_t db = desc_hi(8192, 1024, 1) | desc_lo(st + R1_A);
        wg_fence();
        #pragma unroll
        for (int k = 0; k < 4; k++) {
            wg_ss_n192_tb(a0, da + k * 2, db + k * 128, (ks > 0 || k > 0) ? 1 : 0);
            wg_ss_n192_tb(a1, da + 512 + k * 2, db + k * 128, (ks > 0 || k > 0) ? 1 : 0);
        }
        wg_commit();
        wg_wait<0>();
        mbar_arrive_if(bars + (B_EMPTY1 + s) * 8, elect);
    }
    fence_regs(a0); fence_regs(a1);
    bar_sync(3, 256);
    const int tid = wg * 128 + w4 * 32 + lane;
    if (tid == 0) mbar_arrive(bars + B_R1FREE * 8);
    const int t = lane & 3;
    p1_store_rows<1>(a0, 0, wg, w4, lane, sb); p1_store_vt(a0, 0, wg, w4, lane, sb);
    p1_store_rows<1>(a1, 1, wg, w4, lane, sb); p1_store_vt(a1, 1, wg, w4, lane, sb);
    fence_async_smem();
    publish_norm(fmaxf(quad_norms(a0, 1, t), quad_norms(a1, 1, t)), 1, sp, lane);
    publish_norm(fmaxf(quad_norms(a0, 2, t), quad_norms(a1, 2, t)), 2, sp, lane);
    bar_sync(3, 256);
    if (tid == 0) mbar_arrive(bars + B_KVSTAGED * 8);
    p1_store_rows<0>(a0, 0, wg, w4, lane, sb);
    p1_store_rows<0>(a1, 1, wg, w4, lane, sb);
    fence_async_smem();
    publish_norm(fmaxf(quad_norms(a0, 0, t), quad_norms(a1, 0, t)), 0, sp, lane);
    bar_sync(3, 256);
    if (tid == 0) mbar_arrive(bars + B_P1DONE * 8);
}

__device__ __forceinline__ float exp2_fma(float x) {
    const float MAGIC = 12582912.f;
    const float t = __fadd_rn(x, MAGIC);
    const float f = __fadd_rn(x, -__fadd_rn(t, -MAGIC));
    float p = fmaf(0.0013277939287945628f, f, 0.009675757959485054f);
    p = fmaf(p, f, 0.05550709739327431f);
    p = fmaf(p, f, 0.24022114276885986f);
    p = fmaf(p, f, 0.6931469440460205f);
    p = fmaf(p, f, 1.0000001192092896f);
    return __uint_as_float(__float_as_uint(p) + (__float_as_uint(t) << 23));
}
__device__ __forceinline__ void exp_pack(const float (&s)[32], uint32_t (&p)[16]) {
    #pragma unroll
    for (int i = 0; i < 16; i++)
        p[i] = pack_bf16(ex2(s[2 * i]), (i == 11 || i == 15) ? exp2_fma(s[2 * i + 1]) : ex2(s[2 * i + 1]));
}
__device__ __forceinline__ void qk_issue(float (&s)[32], uint64_t dq, uint64_t dk) {
    wg_ss_n64(s, dq, dk, 0);
    wg_ss_n64(s, dq + 2, dk + 2, 1);
}
__device__ __forceinline__ void pv_issue(float (&o)[20], const uint32_t (&p)[16], uint64_t dv) {
    #pragma unroll
    for (int k = 0; k < 4; k++) wg_rs_n40(o, p[4 * k], p[4 * k + 1], p[4 * k + 2], p[4 * k + 3], dv + 2 * k, 1);
}
__device__ __forceinline__ void online_exp_pack(float (&s)[32], uint32_t (&p)[16], float (&o)[20], float (&mx)[2]) {
    #pragma unroll
    for (int rr = 0; rr < 2; rr++) {
        float m = mx[rr];
        #pragma unroll
        for (int b = 0; b < 8; b++) m = fmaxf(m, fmaxf(s[4 * b + 2 * rr], s[4 * b + 2 * rr + 1]));
        m = fmaxf(m, __shfl_xor_sync(0xffffffffu, m, 1)); m = fmaxf(m, __shfl_xor_sync(0xffffffffu, m, 2));
        const float sc = ex2(mx[rr] - m);
        mx[rr] = m;
        #pragma unroll
        for (int b = 0; b < 5; b++) { o[4 * b + 2 * rr] *= sc; o[4 * b + 2 * rr + 1] *= sc; }
        #pragma unroll
        for (int b = 0; b < 8; b++) p[2 * b + rr] = pack_bf16(ex2(s[4 * b + 2 * rr] - m), ex2(s[4 * b + 2 * rr + 1] - m));
    }
}
__device__ __forceinline__ void attn_stage(const float (&o)[20], uint32_t base, int w4, int lane) {
    uint32_t vl[4], vh[4];
    pack32(o, 0, 0, 1.f / __shfl_sync(0xffffffffu, o[16], lane & ~3), vl);
    pack32(o, 0, 1, 1.f / __shfl_sync(0xffffffffu, o[18], lane & ~3), vh);
    const int mat = lane >> 3, row = w4 * 16 + (mat & 1) * 8 + (lane & 7);
    #pragma unroll
    for (int bp = 0; bp < 2; bp++)
        stsm4(base + row * 64 + (((2 * bp + (mat >> 1)) ^ ((row >> 1) & 3)) << 4), vl[2 * bp], vh[2 * bp], vl[2 * bp + 1], vh[2 * bp + 1]);
}

__device__ __forceinline__ bool scores_bounded(float nq, float nk, float nv) {
    return (nq * nk <= 3600.f) && (nv <= 1e24f) && (nq <= 1e18f) && (nk <= 1e18f);
}
template <int NST, int S0>
__device__ __forceinline__ void attn_body(uint32_t bars, uint32_t par, int s0r, bool elect, uint64_t dqa, uint64_t dqb, uint64_t dkb, uint64_t dvb,
                                          float (&sa)[32], float (&sc)[32], uint32_t (&pa)[16], uint32_t (&pb)[16], float (&oa)[20], float (&ob)[20]) {
    const int s0 = S0 >= 0 ? S0 : s0r;
    #define SLOT(u) (S0 >= 0 ? ((S0 + (u)) & 3) : s0 + (u))
    #define PAR(u) (S0 >= 0 ? par ^ (((S0 + (u)) >> 2) & 1) : par)
    mbar_wait(bars + (B_KVFULL + SLOT(0)) * 8, par);
    wg_fence();
    qk_issue(sa, dqa, dkb + SLOT(0) * (KV_STAGE >> 4)); wg_commit();
    qk_issue(sc, dqb, dkb + SLOT(0) * (KV_STAGE >> 4)); wg_commit();
    #pragma unroll
    for (int q = 0; q < 2 * NST; q++) {
        const int u = q >> 1, half = q & 1, qn = q + 1;
        const uint64_t dv = dvb + SLOT(u) * (KV_STAGE >> 4) + half * (5120 >> 4);
        const uint64_t dkn = dkb + SLOT(qn >> 1) * (KV_STAGE >> 4) + (qn & 1) * (4096 >> 4);
        wg_wait<1>();
        fence_regs(sa);
        exp_pack(sa, pa);
        if (half == 1 && qn < 2 * NST) mbar_wait(bars + (B_KVFULL + SLOT(u + 1)) * 8, PAR(u + 1));
        fence_regs(pa);
        wg_fence();
        pv_issue(oa, pa, dv);
        if (qn < 2 * NST) qk_issue(sa, dqa, dkn);
        wg_commit();
        wg_wait<1>();
        fence_regs(sc);
        if (half == 0 && u > 0) mbar_arrive_if(bars + (B_KVEMPTY + SLOT(u - 1)) * 8, elect);
        exp_pack(sc, pb);
        fence_regs(pb);
        wg_fence();
        pv_issue(ob, pb, dv);
        if (qn < 2 * NST) qk_issue(sc, dqb, dkn);
        wg_commit();
    }
    wg_wait<0>();
    fence_regs(oa); fence_regs(ob);
    mbar_arrive_if(bars + (B_KVEMPTY + SLOT(NST - 1)) * 8, elect);
    #undef SLOT
    #undef PAR
}

__device__ __forceinline__ void attention(uint32_t sb, uint8_t* sp, int wg, int w4, int lane) {
    const uint32_t bars = sb + BAR_OFF;
    const bool elect = (w4 == 0 && lane == 0);
    const volatile float* nloc = (const volatile float*)(sp + NORM_OFF);
    #pragma unroll 1
    for (int task = 0; task < 2; task++) {
        bool fast = true;
        if (task == 0) fast = scores_bounded(nloc[0], nloc[2], nloc[4]);
        const uint64_t dqa = D_K64 | desc_lo(sb + Q_OFF + task * 16384 + wg * 8192), dqb = dqa + 256;
        float oa[20], ob[20], sa[32], sc[32];
        uint32_t pa[16], pb[16];
        #pragma unroll
        for (int i = 0; i < 20; i++) { oa[i] = 0.f; ob[i] = 0.f; }
        fence_regs(oa); fence_regs(ob);
        const uint64_t dkb = D_K64 | desc_lo(sb + KV_OFF), dvb = D_K128 | desc_lo(sb + KV_OFF + 8192);
        int body = 0;
        #pragma unroll 1
        for (; body < 8; body++) {
            if (body == (task == 0 ? 1 : 0)) {
                mbar_wait(bars + B_NORMOK * 8, 0);
                fast = fast && ((*((const volatile unsigned int*)(sp + NORM_OFF) + 8) >> task) & 1u);
            }
            if (!fast) break;
            const uint32_t par = (task * 4 + (body >> 1)) & 1;
            if (task == 0 && body < 2) attn_body<2, -1>(bars, par, body * 2, elect, dqa, dqb, dkb, dvb, sa, sc, pa, pb, oa, ob);
            else { attn_body<4, 0>(bars, par, 0, elect, dqa, dqb, dkb, dvb, sa, sc, pa, pb, oa, ob); body++; }
        }
        if (body < 8) {
            const float m0 = body > 0 ? 0.f : -INFINITY;
            float ma[2] = {m0, m0}, mb[2] = {m0, m0};
            #pragma unroll 1
            for (int q = body * 4; q < 32; q++) {
                const int u = (q >> 1) & 3, half = q & 1;
                const uint32_t par = (task * 4 + (q >> 3)) & 1;
                if (half == 0) mbar_wait(bars + (B_KVFULL + u) * 8, par);
                const uint64_t dk = dkb + u * (KV_STAGE >> 4) + half * (4096 >> 4);
                const uint64_t dv = dvb + u * (KV_STAGE >> 4) + half * (5120 >> 4);
                wg_fence();
                qk_issue(sa, dqa, dk);
                qk_issue(sc, dqb, dk);
                wg_commit();
                wg_wait<0>();
                fence_regs(sa); fence_regs(sc);
                online_exp_pack(sa, pa, oa, ma);
                online_exp_pack(sc, pb, ob, mb);
                fence_regs(pa); fence_regs(pb); fence_regs(oa); fence_regs(ob);
                wg_fence();
                pv_issue(oa, pa, dv);
                pv_issue(ob, pb, dv);
                wg_commit();
                wg_wait<0>();
                fence_regs(oa); fence_regs(ob);
                if (half == 1) mbar_arrive_if(bars + (B_KVEMPTY + u) * 8, elect);
            }
        }
        attn_stage(oa, sb + Q_OFF + task * 16384 + wg * 8192, w4, lane);
        attn_stage(ob, sb + Q_OFF + task * 16384 + wg * 8192 + 4096, w4, lane);
        fence_async_smem();
        __syncwarp();
        mbar_arrive_if(bars + (B_ODONE + wg) * 8, lane == 0);
    }
}

__device__ __forceinline__ void phase3(uint32_t sb, int wg, int w4, int lane, int c, const Params& P) {
    const uint32_t bars = sb + BAR_OFF;
    const bool elect = (w4 == 0 && lane == 0);
    float a0[64], a1[64];
    #pragma unroll 1
    for (int ks = 0; ks < 16; ks++) {
        const int s = ks & 3;
        mbar_wait(bars + (B_FULL3 + s) * 8, (ks >> 2) & 1);
        const uint32_t st = sb + s * R3_STAGE;
        const uint64_t db = desc_hi(8192, 1024, 1) | desc_lo(st + R3_A);
        const uint64_t da = D_K128 | desc_lo(st + wg * 8192);
        wg_fence();
        #pragma unroll
        for (int k = 0; k < 4; k++) {
            wg_ss_n128_tb(a0, da + k * 2, db + k * 128, (ks > 0 || k > 0) ? 1 : 0);
            wg_ss_n128_tb(a1, da + k * 2, db + 1024 + k * 128, (ks > 0 || k > 0) ? 1 : 0);
        }
        wg_commit();
        wg_wait<0>();
        mbar_arrive_if(bars + (B_EMPTY3 + s) * 8, elect);
    }
    fence_regs(a0); fence_regs(a1);
    const int br = c >> 6, rb = c & 15, cb = (c >> 4) & 3;
    bar_sync(3, 256);
    const uint32_t stg = sb + wg * 32768;
    const int mat = lane >> 3, row = w4 * 16 + (mat & 1) * 8 + (lane & 7);
    #pragma unroll
    for (int g = 0; g < 4; g++) {
        #pragma unroll
        for (int bp = 0; bp < 4; bp++) {
            const int b = (g & 1) * 8 + 2 * bp;
            const uint32_t ad = stg + g * 8192 + row * 128 + (((2 * bp + (mat >> 1)) ^ (lane & 7)) << 4);
            if (g < 2) stsm4(ad, pack_bf16(a0[4 * b], a0[4 * b + 1]), pack_bf16(a0[4 * b + 2], a0[4 * b + 3]), pack_bf16(a0[4 * b + 4], a0[4 * b + 5]), pack_bf16(a0[4 * b + 6], a0[4 * b + 7]));
            else stsm4(ad, pack_bf16(a1[4 * b], a1[4 * b + 1]), pack_bf16(a1[4 * b + 2], a1[4 * b + 3]), pack_bf16(a1[4 * b + 4], a1[4 * b + 5]), pack_bf16(a1[4 * b + 6], a1[4 * b + 7]));
        }
        fence_async_smem();
        bar_sync(1 + wg, 128);
        if (elect) { tma2d_store(&P.out, stg + g * 8192, br * 1024 + cb * 256 + g * 64, rb * 128 + wg * 64); bulk_commit(); }
    }
    if (elect) bulk_wait_all();
}

__device__ __forceinline__ uint32_t hmax2(uint32_t a, uint32_t b) { uint32_t r; asm("max.bf16x2 %0, %1, %2;" : "=r"(r) : "r"(a), "r"(b)); return r; }
__device__ __forceinline__ uint32_t hmin2(uint32_t a, uint32_t b) { uint32_t r; asm("min.bf16x2 %0, %1, %2;" : "=r"(r) : "r"(a), "r"(b)); return r; }
__device__ __forceinline__ float rcp(float x) { float y; asm("rcp.approx.ftz.f32 %0, %1;" : "=f"(y) : "f"(x)); return y; }
__device__ __forceinline__ void feature_map(const float (&px)[16], uint32_t (&F)[8][2]) {
    const float L2E = 1.4426950408889634f;
    #pragma unroll
    for (int rr = 0; rr < 2; rr++) {
        uint32_t pk[4];
        #pragma unroll
        for (int b = 0; b < 4; b++) pk[b] = pack_bf16(px[4 * b + 2 * rr], px[4 * b + 2 * rr + 1]);
        const uint32_t m2 = hmax2(hmax2(pk[0], pk[1]), hmax2(pk[2], pk[3]));
        const uint32_t n2 = hmin2(hmin2(pk[0], pk[1]), hmin2(pk[2], pk[3])) ^ 0x80008000u;
        uint32_t t = hmax2(__byte_perm(m2, n2, 0x5410), __byte_perm(m2, n2, 0x7632));
        t = hmax2(t, __shfl_xor_sync(0xffffffffu, t, 1));
        t = hmax2(t, __shfl_xor_sync(0xffffffffu, t, 2));
        const float nmx = -bf_lo(t) * L2E, pmn = -bf_hi(t) * L2E;
        float x[8];
        #pragma unroll
        for (int b = 0; b < 4; b++) { x[2 * b] = bf_lo(pk[b]); x[2 * b + 1] = bf_hi(pk[b]); }
        float ep[8], en[8], sp = 0.f, sn = 0.f;
        #pragma unroll
        for (int i = 0; i < 8; i++) {
            ep[i] = ex2(fmaf(x[i], L2E, nmx)); en[i] = ex2(fmaf(x[i], -L2E, pmn));
            sp += ep[i]; sn += en[i];
        }
        sp += __shfl_xor_sync(0xffffffffu, sp, 1); sn += __shfl_xor_sync(0xffffffffu, sn, 1);
        sp += __shfl_xor_sync(0xffffffffu, sp, 2); sn += __shfl_xor_sync(0xffffffffu, sn, 2);
        const float ip = rcp(sp), in = rcp(sn);
        #pragma unroll
        for (int b = 0; b < 4; b++) {
            F[b][rr] = pack_bf16(ep[2 * b] * ip, ep[2 * b + 1] * ip);
            F[4 + b][rr] = pack_bf16(en[2 * b] * in, en[2 * b + 1] * in);
        }
    }
}

__device__ __forceinline__ void a_epilogue(const float (&a)[96], uint32_t sb, int w4, int lane, int tile, int j) {
    const int mat = lane >> 3, i = lane & 7;
    const uint32_t scr = sb + SCR_OFF;
    const uint64_t dw0 = D_K64 | desc_lo(sb + WPHI_OFF), dw1 = dw0 + 128;
    {
        uint32_t fk[16];
        #pragma unroll
        for (int q = 0; q < 16; q++) fk[q] = pack_bf16(a[32 + 2 * q], a[32 + 2 * q + 1]);
        float px0[16], px1[16];
        fence_regs(fk);
        wg_fence();
        wg_rs_n32(px0, fk[0], fk[1], fk[2], fk[3], dw0, 0);
        wg_rs_n32(px0, fk[4], fk[5], fk[6], fk[7], dw0 + 2, 1);
        wg_rs_n32(px1, fk[8], fk[9], fk[10], fk[11], dw1, 0);
        wg_rs_n32(px1, fk[12], fk[13], fk[14], fk[15], dw1 + 2, 1);
        wg_commit();
        #pragma unroll
        for (int hh = 0; hh < 2; hh++) {
            uint32_t vl[4], vh[4];
            pack32(a, 16 + hh * 4, 0, 1.f, vl);
            pack32(a, 16 + hh * 4, 1, 1.f, vh);
            #pragma unroll
            for (int bp = 0; bp < 2; bp++) {
                const int rowd = 8 * (2 * bp + (mat >> 1)) + i, chunk = 2 * w4 + (mat & 1);
                stsm4_t(scr + 16384 + hh * 5120 + rowd * 128 + ((chunk ^ i) << 4), vl[2 * bp], vh[2 * bp], vl[2 * bp + 1], vh[2 * bp + 1]);
            }
        }
        #pragma unroll
        for (int kk = 0; kk < 4; kk++)
            g_qfrag[(size_t)(tile * 4 + kk) * 128 + w4 * 32 + lane] = make_uint4(pack_bf16(a[8 * kk], a[8 * kk + 1]), pack_bf16(a[8 * kk + 2], a[8 * kk + 3]),
                                                                                  pack_bf16(a[8 * kk + 4], a[8 * kk + 5]), pack_bf16(a[8 * kk + 6], a[8 * kk + 7]));
        wg_wait<0>();
        fence_regs(px0); fence_regs(px1);
        uint32_t F0[8][2], F1[8][2];
        feature_map(px0, F0);
        feature_map(px1, F1);
        #pragma unroll
        for (int bp = 0; bp < 4; bp++) {
            const int srow = w4 * 16 + (mat & 1) * 8 + i, chunk = 2 * bp + (mat >> 1);
            const uint32_t ad = scr + srow * 128 + ((chunk ^ i) << 4);
            stsm4(ad, F0[2 * bp][0], F0[2 * bp][1], F0[2 * bp + 1][0], F0[2 * bp + 1][1]);
            stsm4(ad + 8192, F1[2 * bp][0], F1[2 * bp][1], F1[2 * bp + 1][0], F1[2 * bp + 1][1]);
        }
    }
    fence_async_smem();
    bar_sync(4, 128);
    float kv0[20], kv1[20];
    {
        const uint64_t dA0 = desc_hi(8192, 1024, 1) | desc_lo(scr), dA1 = dA0 + 512;
        const uint64_t dB0 = D_K128 | desc_lo(scr + 16384), dB1 = dB0 + 320;
        wg_fence();
        #pragma unroll
        for (int k = 0; k < 4; k++) wg_ss_n40_ta(kv0, dA0 + k * 128, dB0 + k * 2, k > 0 ? 1 : 0);
        #pragma unroll
        for (int k = 0; k < 4; k++) wg_ss_n40_ta(kv1, dA1 + k * 128, dB1 + k * 2, k > 0 ? 1 : 0);
        wg_commit();
        wg_wait<0>();
        fence_regs(kv0); fence_regs(kv1);
    }
    #pragma unroll
    for (int hh = 0; hh < 2; hh++) {
        float* dst = g_kv + (size_t)((2 * j + hh) * 64 + w4 * 16 + (lane >> 2)) * 40 + (lane & 3) * 2;
        #pragma unroll
        for (int b = 0; b < 5; b++) {
            if (b < 4 || (lane & 3) == 0) {
                #pragma unroll
                for (int rr = 0; rr < 2; rr++) {
                    const float v0 = hh == 0 ? kv0[4 * b + 2 * rr] : kv1[4 * b + 2 * rr], v1 = hh == 0 ? kv0[4 * b + 2 * rr + 1] : kv1[4 * b + 2 * rr + 1];
                    asm volatile("red.global.add.v2.f32 [%0], {%1, %2};" :: "l"(dst + rr * 8 * 40 + b * 8), "f"(v0), "f"(v1) : "memory");
                }
            }
        }
    }
}

__device__ __forceinline__ void phi_q_issue(uint32_t (&fq)[16], uint64_t dw0, uint64_t dw1, float (&px0)[16], float (&px1)[16]) {
    wg_rs_n32(px0, fq[0], fq[1], fq[2], fq[3], dw0, 0);
    wg_rs_n32(px0, fq[4], fq[5], fq[6], fq[7], dw0 + 2, 1);
    wg_rs_n32(px1, fq[8], fq[9], fq[10], fq[11], dw1, 0);
    wg_rs_n32(px1, fq[12], fq[13], fq[14], fq[15], dw1 + 2, 1);
}
__device__ __forceinline__ void load_qfrag(uint32_t (&fq)[16], int tile, int tid) {
    #pragma unroll
    for (int q = 0; q < 4; q++) {
        const uint4 v = __ldcg(&g_qfrag[(size_t)(tile * 4 + q) * 128 + tid]);
        fq[4 * q] = v.x; fq[4 * q + 1] = v.y; fq[4 * q + 2] = v.z; fq[4 * q + 3] = v.w;
    }
}

__device__ __forceinline__ void a_branch(uint32_t sb, uint8_t* sp, int w4, int lane, int r, int j, unsigned int epoch, const Params& P) {
    const uint32_t bars = sb + BAR_OFF;
    const int tid = w4 * 32 + lane;
    const bool elect = (tid == 0);
    for (int i = tid; i < 2 * 256; i += 128) {
        const int hh = i >> 8, w = i & 255;
        *(uint32_t*)(sp + SCR_OFF + 16384 + hh * 5120 + 4096 + w * 4) = (w < 32) ? 0x3F803F80u : 0u;
    }
    #pragma unroll 1
    for (int i = 0; i < 4; i++) {
        float a[96];
        #pragma unroll
        for (int q = 0; q < 96; q++) a[q] = 0.f;
        fence_regs(a);
        const uint64_t da0 = D_K128 | desc_lo(sb + GX_OFF), db0 = desc_hi(4096, 1024, 1) | desc_lo(sb);
        #pragma unroll 1
        for (int ks = 0; ks < 32; ks += 8) {
            #pragma unroll
            for (int u = 0; u < 8; u++) {
                mbar_wait(bars + (B_GFULL + (u & 3)) * 8, (u >> 2) & 1);
                const uint64_t da = da0 + (((u >> 1) & 3) * GX_STAGE + (u & 1) * 64 >> 4), db = db0 + ((u & 3) * GW_STAGE >> 4);
                wg_fence();
                wg_ss_n192_tb(a, da, db, 1);
                wg_ss_n192_tb(a, da + 2, db + 128, 1);
                wg_commit();
                wg_wait<1>();
                mbar_arrive_if(bars + (B_GEMPTY + ((u + 3) & 3)) * 8, elect && (u > 0 || ks > 0));
                if ((u & 3) == 2) wg_wait<0>();
            }
        }
        wg_wait<0>();
        mbar_arrive_if(bars + (B_GEMPTY + 3) * 8, elect);
        fence_regs(a);
        if (i == 0) { if (elect) flag_wait(&g_cntB[j], 8 * (epoch + 1)); }
        bar_sync(4, 128);
        a_epilogue(a, sb, w4, lane, (r * 4 + i) * 16 + j, j);
    }
    bar_sync(4, 128);
    if (elect) mbar_arrive(bars + B_KVDONE * 8);
    const uint64_t dw0 = D_K64 | desc_lo(sb + WPHI_OFF), dw1 = dw0 + 128;
    uint32_t F0[8][2], F1[8][2], fq[16];
    {
        float px0[16], px1[16];
        load_qfrag(fq, (r * 4) * 16 + j, tid);
        fence_regs(fq);
        wg_fence();
        phi_q_issue(fq, dw0, dw1, px0, px1);
        wg_commit();
        wg_wait<0>();
        fence_regs(px0); fence_regs(px1);
        load_qfrag(fq, (r * 4 + 1) * 16 + j, tid);
        feature_map(px0, F0);
        feature_map(px1, F1);
    }
    if (elect) flag_wait(&g_cntA[j], 8 * (epoch + 1));
    bar_sync(4, 128);
    {
        const int hh = tid >> 6, fp = (tid >> 1) & 31, half = tid & 1, f = fp * 2;
        const float4* src0 = (const float4*)(g_kv + (size_t)((2 * j + hh) * 64 + f) * 40 + half * 20);
        float4 v0[5], v1[5];
        #pragma unroll
        for (int q = 0; q < 5; q++) { v0[q] = __ldcg(src0 + q); v1[q] = __ldcg(src0 + 10 + q); }
        #pragma unroll
        for (int q = 0; q < 5; q++) {
            const float e0[4] = {v0[q].x, v0[q].y, v0[q].z, v0[q].w}, e1[4] = {v1[q].x, v1[q].y, v1[q].z, v1[q].w};
            #pragma unroll
            for (int e = 0; e < 4; e++) {
                const int n = half * 20 + q * 4 + e;
                *(uint32_t*)(sp + SCR_OFF + hh * 5120 + n * 128 + (((f >> 3) ^ (n & 7)) << 4) + (f & 7) * 2) = n <= 32 ? pack_bf16(e0[e], e1[e]) : 0u;
            }
        }
    }
    fence_async_smem();
    bar_sync(4, 128);
    {
        const uint64_t dB0 = D_K128 | desc_lo(sb + SCR_OFF), dB1 = dB0 + 320;
        #pragma unroll 1
        for (int i = 0; i < 4; i++) {
            float o0[20], o1[20], px0[16], px1[16];
            #pragma unroll
            for (int b = 0; b < 8; b++) { fence_regs(F0[b]); fence_regs(F1[b]); }
            fence_regs(fq);
            wg_fence();
            #pragma unroll
            for (int kk = 0; kk < 4; kk++) wg_rs_n40(o0, F0[2 * kk][0], F0[2 * kk][1], F0[2 * kk + 1][0], F0[2 * kk + 1][1], dB0 + 2 * kk, kk > 0 ? 1 : 0);
            #pragma unroll
            for (int kk = 0; kk < 4; kk++) wg_rs_n40(o1, F1[2 * kk][0], F1[2 * kk][1], F1[2 * kk + 1][0], F1[2 * kk + 1][1], dB1 + 2 * kk, kk > 0 ? 1 : 0);
            phi_q_issue(fq, dw0, dw1, px0, px1);
            wg_commit();
            wg_wait<0>();
            fence_regs(o0); fence_regs(o1); fence_regs(px0); fence_regs(px1);
            load_qfrag(fq, (r * 4 + (i + 2 < 4 ? i + 2 : 3)) * 16 + j, tid);
            #pragma unroll
            for (int hh = 0; hh < 2; hh++) {
                uint32_t vl[4];
                #pragma unroll
                for (int rr = 0; rr < 2; rr++) {
                    float den = __shfl_sync(0xffffffffu, hh == 0 ? o0[16 + 2 * rr] : o1[16 + 2 * rr], lane & ~3);
                    den = bf_round(bf_round(den) + 1e-6f);
                    const float inv = rcp(den);
                    uint32_t v[4];
                    #pragma unroll
                    for (int b = 0; b < 4; b++) {
                        const uint32_t pk = hh == 0 ? pack_bf16(o0[4 * b + 2 * rr], o0[4 * b + 2 * rr + 1]) : pack_bf16(o1[4 * b + 2 * rr], o1[4 * b + 2 * rr + 1]);
                        v[b] = pack_bf16(bf_lo(pk) * inv, bf_hi(pk) * inv);
                    }
                    if (rr == 0) { vl[0] = v[0]; vl[1] = v[1]; vl[2] = v[2]; vl[3] = v[3]; }
                    else {
                        const int srow = (i & 1) * 64 + w4 * 16 + ((lane >> 3) & 1) * 8 + (lane & 7);
                        #pragma unroll
                        for (int bp = 0; bp < 2; bp++)
                            stsm4(sb + (i >> 1) * 16384 + srow * 128 + (((hh * 4 + 2 * bp + (lane >> 4)) ^ (lane & 7)) << 4), vl[2 * bp], v[2 * bp], vl[2 * bp + 1], v[2 * bp + 1]);
                    }
                }
            }
            if (i == 3) break;
            feature_map(px0, F0);
            feature_map(px1, F1);
        }
    }
    fence_async_smem();
    bar_sync(4, 128);
    if (elect) {
        for (int u = 0; u < 2; u++) tma2d_store(&P.o, sb + u * 16384, j * 64, r * 256 + u * 128);
        bulk_commit();
        bulk_wait_all();
        mbar_arrive(bars + B_ADONE * 8);
        asm volatile("fence.proxy.async.global;" ::: "memory");
        flag_signal_relaxed(&g_cntOA[r]);
    }
}

__global__ void __launch_bounds__(512, 1) fused_kernel(const __grid_constant__ Params P) {
    extern __shared__ uint8_t smem_raw[];
    const uint32_t sb = (smem_u32(smem_raw) + 1023) & ~1023u;
    uint8_t* sp = smem_raw + (sb - smem_u32(smem_raw));
    const uint32_t bars = sb + BAR_OFF;
    const int c = blockIdx.x, r = c & 7, j = c >> 3;
    if (threadIdx.x == 384) {
        for (int s = 0; s < R1_N; s++) { mbar_init(bars + (B_FULL1 + s) * 8, 1); mbar_init(bars + (B_EMPTY1 + s) * 8, 2); }
        asm volatile("fence.mbarrier_init.release.cluster;" ::: "memory");
        fence_async_smem();
        for (int ks = 0; ks < R1_N; ks++) {
            const uint32_t st = sb + ks * R1_STAGE, fb = bars + (B_FULL1 + ks) * 8;
            mbar_expect_tx(fb, R1_STAGE);
            tma2d(st, &P.xB, ks * 64, r * 256, fb);
            tma3d(st + R1_A, &P.wB, j * 64, ks * 64, 0, fb);
        }
    }
    if (threadIdx.x < 120) {
        const int i = threadIdx.x;
        const char* src = i < 48 ? (const char*)P.pxB + (size_t)(r * 256 + j * 16 + i / 3) * 2048 + (i % 3) * 128
                                 : (const char*)P.pwB + (size_t)(r * 24 + (i - 48) / 3) * 6144 + ((i - 48) % 3) * 2048 + j * 128;
        asm volatile("prefetch.global.L2 [%0];" :: "l"(src));
    }
    const int warp = __shfl_sync(0xffffffffu, (int)(threadIdx.x >> 5), 0), lane = threadIdx.x & 31, wg = warp >> 2, w4 = warp & 3;
    const unsigned int epoch = __ldcg(&g_epoch[c]);
    if (threadIdx.x == 416) { prefetch_map(&P.xA); prefetch_map(&P.wA); prefetch_map(&P.o); prefetch_map(&P.oS); prefetch_map(&P.woA); prefetch_map(&P.woB); prefetch_map(&P.out); }
    if (threadIdx.x == 0) {
        for (int s = 0; s < KV_N; s++) { mbar_init(bars + (B_KVFULL + s) * 8, 1); mbar_init(bars + (B_KVEMPTY + s) * 8, 2); }
        for (int s = 0; s < G_N; s++) { mbar_init(bars + (B_GFULL + s) * 8, 1); mbar_init(bars + (B_GEMPTY + s) * 8, 1); }
        for (int q = 0; q < 6; q++) *((unsigned int*)(sp + NORM_OFF) + q) = 0u;
    }
    if (threadIdx.x == 32) {
        for (int s = 0; s < R3_N; s++) { mbar_init(bars + (B_FULL3 + s) * 8, 1); mbar_init(bars + (B_EMPTY3 + s) * 8, 2); }
        mbar_init(bars + B_R1FREE * 8, 1); mbar_init(bars + B_P1DONE * 8, 1); mbar_init(bars + B_P2DONE * 8, 2); mbar_init(bars + B_ADONE * 8, 1);
        mbar_init(bars + B_NORMOK * 8, 1); mbar_init(bars + B_ODONE * 8, 4); mbar_init(bars + (B_ODONE + 1) * 8, 4);
        mbar_init(bars + B_KVDONE * 8, 1); mbar_init(bars + B_KVSTAGED * 8, 2);
    }
    if (threadIdx.x == 0 || threadIdx.x == 32) asm volatile("fence.mbarrier_init.release.cluster;" ::: "memory");
    __syncthreads();

    if (wg == 3) {
        reg_dealloc<24>();
        if (warp == 12) {
            for (int ks = R1_N; ks < 16; ks++) {
                const int s = ks % R1_N;
                mbar_wait(bars + (B_EMPTY1 + s) * 8, ((ks / R1_N) - 1) & 1);
                const uint32_t st = sb + s * R1_STAGE, fb = bars + (B_FULL1 + s) * 8;
                if (elect_one()) {
                    mbar_expect_tx(fb, R1_STAGE);
                    tma2d(st, &P.xB, ks * 64, r * 256, fb);
                    tma3d(st + R1_A, &P.wB, j * 64, ks * 64, 0, fb);
                    if (ks >= 3 && ks < 13) {
                        const int q = ks - 3;
                        const char* src = q < 6 ? (const char*)P.pwA + (size_t)c * 49152 + q * 8192 : (const char*)P.pxA + (size_t)c * 32768 + (q - 6) * 8192;
                        asm volatile("cp.async.bulk.prefetch.L2.global [%0], %1;" :: "l"(src), "r"(8192u) : "memory");
                    }
                }
                __syncwarp();
            }
            mbar_wait_long(bars + B_KVSTAGED * 8, 0);
            if (lane == 0) {
                for (int q = 0; q < 4; q++) {
                    const int hh = q >> 1, w = q & 1;
                    const uint32_t st = sb + KV_OFF + q * KV_STAGE;
                    bulk_store(&g_kimg[(size_t)((2 * j + hh) * 16 + 2 * r + w) * 512], st, 8192);
                    bulk_store(&g_vimg[(size_t)((2 * j + hh) * 32 + (2 * r + w) * 2) * 256], st + 8192, 4096);
                    bulk_store(&g_vimg[(size_t)((2 * j + hh) * 32 + (2 * r + w) * 2 + 1) * 256], st + 8192 + 5120, 4096);
                    if (q & 1) bulk_commit();
                }
                {
                    float chk = 0.f;
                    for (int q = 0; q < 4; q++) {
                        float* dst = &g_norm[((q >> 1) * NH + 2 * j + (q & 1)) * 8 + r];
                        asm volatile("st.relaxed.gpu.global.f32 [%0], %1;" :: "l"(dst), "f"(__uint_as_float(*((volatile unsigned int*)(sp + NORM_OFF) + 2 + q))) : "memory");
                        float v; asm volatile("ld.relaxed.gpu.global.f32 %0, [%1];" : "=f"(v) : "l"(dst) : "memory");
                        chk += v;
                    }
                    asm volatile("" :: "f"(chk) : "memory");
                }
                asm volatile("cp.async.bulk.wait_group 1;" ::: "memory");
                asm volatile("fence.proxy.async.global;" ::: "memory");
                flag_signal_relaxed(&g_cntB[j]);
                asm volatile("cp.async.bulk.wait_group.read 0;" ::: "memory");
                flag_wait(&g_cntB[j], 8 * (epoch + 1));
                asm volatile("fence.proxy.async.global;" ::: "memory");
            }
            __syncwarp();
            for (int g = 2; g < 32; g++) {
                const int s = g & 3, h = 2 * j + (g >> 4), t = (2 * r + g) & 15;
                if (g >= KV_N) mbar_wait_long(bars + (B_KVEMPTY + s) * 8, ((g >> 2) - 1) & 1);
                const uint32_t st = sb + KV_OFF + s * KV_STAGE, fb = bars + (B_KVFULL + s) * 8;
                if (elect_one()) {
                    mbar_expect_tx(fb, 16384);
                    bulk_load(st, &g_kimg[(size_t)(h * 16 + t) * 512], 8192, fb);
                    bulk_load(st + 8192, &g_vimg[(size_t)(h * 32 + 2 * t) * 256], 4096, fb);
                    bulk_load(st + 8192 + 5120, &g_vimg[(size_t)(h * 32 + 2 * t + 1) * 256], 4096, fb);
                    if (g >= 8 && g < 12) {
                        const char* src = (g < 10 ? (const char*)P.pwoA : (const char*)P.pwoB) + (size_t)c * 16384 + (g & 1) * 8192;
                        asm volatile("cp.async.bulk.prefetch.L2.global [%0], %1;" :: "l"(src), "r"(8192u) : "memory");
                    }
                }
                __syncwarp();
                if (g == 3) {
                    if (lane == 0) {
                        bulk_wait_all();
                        asm volatile("fence.proxy.async.global;" ::: "memory");
                        flag_signal_relaxed(&g_cntB[16 + j]);
                    }
                    __syncwarp();
                }
                if (g == 15) {
                    if (lane == 0) { flag_wait(&g_cntB[16 + j], 8 * (epoch + 1)); asm volatile("fence.proxy.async.global;" ::: "memory"); }
                    __syncwarp();
                }
            }
            const int br = c >> 6, rb = c & 15, cb = (c >> 4) & 3;
            for (int ks = 0; ks < 16; ks++) {
                const int s = ks & 3;
                if (ks == 0) {
                    mbar_wait_long(bars + B_ADONE * 8, 0);
                    if (lane == 0) {
                        if (br == 0) flag_wait(&g_cntOA[rb >> 1], 16 * (epoch + 1)); else flag_wait(&g_cntOB[rb >> 1], 32 * (epoch + 1));
                        asm volatile("fence.proxy.async.global;" ::: "memory");
                    }
                    __syncwarp();
                }
                if (ks == 1) mbar_wait(bars + (B_KVEMPTY + 0) * 8, 1);
                if (ks == 2) { mbar_wait(bars + (B_KVEMPTY + 1) * 8, 1); mbar_wait(bars + (B_KVEMPTY + 2) * 8, 1); mbar_wait(bars + (B_KVEMPTY + 3) * 8, 1); }
                if (ks == 3) mbar_wait(bars + B_P2DONE * 8, 0);
                if (ks == 8 && br == 1) {
                    if (lane == 0) { flag_wait(&g_cntOB[8 + (rb >> 1)], 32 * (epoch + 1)); asm volatile("fence.proxy.async.global;" ::: "memory"); }
                    __syncwarp();
                }
                if (ks >= R3_N) mbar_wait(bars + (B_EMPTY3 + s) * 8, ((ks >> 2) - 1) & 1);
                const uint32_t st = sb + s * R3_STAGE, fb = bars + (B_FULL3 + s) * 8;
                if (elect_one()) {
                    mbar_expect_tx(fb, R3_STAGE);
                    tma2d(st, &P.o, ks * 64, br * SEQ + rb * 128, fb);
                    if (br == 0) tma3d(st + R3_A, &P.woA, 0, ks * 64, cb * 4, fb);
                    else tma5d(st + R3_A, &P.woB, 0, 0, ks >> 3, 2 * (ks & 7), cb * 4, fb);
                }
                __syncwarp();
            }
        } else if (warp == 13) {
            mbar_wait_long(bars + B_R1FREE * 8, 0);
            for (int it = 0; it < 128; it++) {
                const int s = it & 3, i = it >> 5, ks = it & 31;
                if (it >= G_N) mbar_wait(bars + (B_GEMPTY + s) * 8, ((it >> 2) - 1) & 1);
                const uint32_t fb = bars + (B_GFULL + s) * 8;
                if (elect_one()) {
                    mbar_expect_tx(fb, (it & 1) ? GW_STAGE : GW_STAGE + GX_STAGE);
                    if (!(it & 1)) tma2d(sb + GX_OFF + ((it >> 1) & 3) * GX_STAGE, &P.xA, ks * 32, r * 256 + i * 64, fb);
                    tma3d(sb + s * GW_STAGE, &P.wA, j * 64, ks * 32, 0, fb);
                }
                __syncwarp();
            }
        } else if (warp == 15) {
            if (lane == 0) {
                for (int q = 0; q < 4; q++) {
                    const int w = q & 1, task = q >> 1;
                    mbar_wait_long(bars + (B_ODONE + w) * 8, task);
                    tma2d_store(&P.oS, sb + Q_OFF + task * 16384 + w * 8192, task * 512 + j * 32, SEQ + r * 256 + w * 128);
                    bulk_commit();
                    bulk_wait_all();
                    if (task == 1) mbar_arrive(bars + B_P2DONE * 8);
                    asm volatile("fence.proxy.async.global;" ::: "memory");
                    flag_signal_relaxed(&g_cntOB[task * 8 + r]);
                }
            }
        } else {
            mbar_wait_long(bars + B_R1FREE * 8, 0);
            for (int i = lane; i < KV_N * 2 * 64; i += 32) {
                const int w = i & 63;
                *(uint4*)(sp + KV_OFF + (i >> 7) * KV_STAGE + 8192 + ((i >> 6) & 1) * 5120 + 4096 + w * 16) =
                    w < 8 ? make_uint4(0x3F803F80u, 0x3F803F80u, 0x3F803F80u, 0x3F803F80u) : make_uint4(0u, 0u, 0u, 0u);
            }
            fence_async_smem();
            __syncwarp();
            if (lane == 0) {
                mbar_wait(bars + B_KVSTAGED * 8, 0);
                mbar_arrive(bars + (B_KVFULL + 0) * 8);
                mbar_arrive(bars + (B_KVFULL + 1) * 8);
                flag_wait(&g_cntB[j], 8 * (epoch + 1));
            }
            __syncwarp();
            {
                float v = __ldcg(&g_norm[((lane >> 4) * NH + 2 * j + ((lane >> 3) & 1)) * 8 + (lane & 7)]);
                v = fmaxf(v, __shfl_xor_sync(0xffffffffu, v, 1)); v = fmaxf(v, __shfl_xor_sync(0xffffffffu, v, 2)); v = fmaxf(v, __shfl_xor_sync(0xffffffffu, v, 4));
                const float nk0 = __shfl_sync(0xffffffffu, v, 0), nk1 = __shfl_sync(0xffffffffu, v, 8), nv0 = __shfl_sync(0xffffffffu, v, 16), nv1 = __shfl_sync(0xffffffffu, v, 24);
                mbar_wait(bars + B_P1DONE * 8, 0);
                if (lane == 0) {
                    const volatile float* nloc = (const volatile float*)(sp + NORM_OFF);
                    *((volatile unsigned int*)(sp + NORM_OFF) + 8) = (scores_bounded(nloc[0], nk0, nv0) ? 1u : 0u) | (scores_bounded(nloc[1], nk1, nv1) ? 2u : 0u);
                    mbar_arrive(bars + B_NORMOK * 8);
                    mbar_wait_long(bars + B_KVDONE * 8, 0);
                    flag_signal(&g_cntA[j]);
                }
            }
        }
    } else if (wg == 2) {
        reg_dealloc<24>();
        for (int i = threadIdx.x & 127; i < 2048; i += 128) {
            const int hh = i >> 10, d = (i >> 5) & 31, f = i & 31;
            *(__nv_bfloat16*)(sp + WPHI_OFF + hh * 2048 + f * 64 + (((d >> 3) ^ ((f >> 1) & 3)) << 4) + (d & 7) * 2) = P.wphi[(size_t)(2 * j + hh) * 1024 + d * 32 + f];
        }
        fence_async_smem();
        if (r == 0) {
            float4* z = (float4*)(g_kv + (size_t)2 * j * 64 * 40);
            for (int i = threadIdx.x & 127; i < 2 * 64 * 40 / 4; i += 128) z[i] = make_float4(0.f, 0.f, 0.f, 0.f);
            __threadfence();
        }
        bar_sync(4, 128);
        if ((threadIdx.x & 127) == 0) mbar_arrive(bars + B_KVSTAGED * 8);
        mbar_wait_long(bars + B_P1DONE * 8, 0);
        reg_alloc<152>();
        a_branch(sb, sp, w4, lane, r, j, epoch, P);
    } else {
        reg_alloc<232>();
        phase1(sb, sp, wg, w4, lane);
        reg_dealloc<168>();
        attention(sb, sp, wg, w4, lane);
        phase3(sb, wg, w4, lane, c, P);
        if (threadIdx.x == 0) g_epoch[c] = epoch + 1;
    }
}

typedef CUresult (*EncodeFn)(CUtensorMap*, CUtensorMapDataType, cuuint32_t, void*, const cuuint64_t*, const cuuint64_t*, const cuuint32_t*,
                             const cuuint32_t*, CUtensorMapInterleave, CUtensorMapSwizzle, CUtensorMapL2promotion, CUtensorMapFloatOOBfill);
static void make_map(EncodeFn enc, CUtensorMap* m, const void* ptr, uint64_t inner, uint64_t outer, uint32_t box_inner, uint32_t box_outer, CUtensorMapSwizzle swz) {
    cuuint64_t gd[2] = {inner, outer}; cuuint64_t gs[1] = {inner * 2}; cuuint32_t bd[2] = {box_inner, box_outer}; cuuint32_t es[2] = {1, 1};
    enc(m, CU_TENSOR_MAP_DATA_TYPE_BFLOAT16, 2, const_cast<void*>(ptr), gd, gs, bd, es, CU_TENSOR_MAP_INTERLEAVE_NONE, swz,
        CU_TENSOR_MAP_L2_PROMOTION_L2_128B, CU_TENSOR_MAP_FLOAT_OOB_FILL_NONE);
}

struct Dims { uint64_t v[5]; };
static void make_map_nd(EncodeFn enc, CUtensorMap* m, const void* ptr, int rank, Dims dims, Dims strides, Dims box) {
    cuuint64_t gd[5], gs[5]; cuuint32_t bd[5], es[5];
    for (int i = 0; i < 5; i++) { gd[i] = dims.v[i]; gs[i] = strides.v[i]; bd[i] = (cuuint32_t)box.v[i]; es[i] = 1; }
    enc(m, CU_TENSOR_MAP_DATA_TYPE_BFLOAT16, rank, const_cast<void*>(ptr), gd, gs, bd, es, CU_TENSOR_MAP_INTERLEAVE_NONE, CU_TENSOR_MAP_SWIZZLE_128B,
        CU_TENSOR_MAP_L2_PROMOTION_L2_128B, CU_TENSOR_MAP_FLOAT_OOB_FILL_NONE);
}

}

extern "C" void kernel_launch(void* const* d_in, const int* in_sizes, int n_in, void* d_out, int out_size) {
    using namespace hk;
    (void)in_sizes; (void)n_in; (void)out_size;
    const __nv_bfloat16* A_x = (const __nv_bfloat16*)d_in[0];
    const __nv_bfloat16* A_wqkv = (const __nv_bfloat16*)d_in[1];
    const __nv_bfloat16* A_wphi = (const __nv_bfloat16*)d_in[2];
    const __nv_bfloat16* A_wo = (const __nv_bfloat16*)d_in[3];
    const __nv_bfloat16* B_x = (const __nv_bfloat16*)d_in[4];
    const __nv_bfloat16* B_wqkv = (const __nv_bfloat16*)d_in[5];
    const __nv_bfloat16* B_wo = (const __nv_bfloat16*)d_in[6];
    static EncodeFn enc = nullptr;
    static void* p_o = nullptr;
    if (!enc) {
        void* fn = nullptr; cudaDriverEntryPointQueryResult qr;
        cudaGetDriverEntryPoint("cuTensorMapEncodeTiled", &fn, cudaEnableDefault, &qr);
        enc = (EncodeFn)fn;
        cudaGetSymbolAddress(&p_o, g_o);
        cudaFuncSetAttribute(fused_kernel, cudaFuncAttributeMaxDynamicSharedMemorySize, SMEM_BYTES);
    }
    Params P;
    const CUtensorMapSwizzle S128 = CU_TENSOR_MAP_SWIZZLE_128B, S64 = CU_TENSOR_MAP_SWIZZLE_64B;
    make_map(enc, &P.xB, B_x, DM, SEQ, 64, 256, S128);
    make_map_nd(enc, &P.wB, B_wqkv, 3, {DM, DM, 3}, {3 * DM * 2, DM * 2}, {64, 64, 3});
    make_map(enc, &P.xA, A_x, DM, SEQ, 64, 64, S128);
    make_map_nd(enc, &P.wA, A_wqkv, 3, {DM, DM, 3}, {3 * DM * 2, DM * 2}, {64, 32, 3});
    make_map(enc, &P.o, p_o, DM, 2 * SEQ, 64, 128, S128);
    make_map(enc, &P.oS, p_o, DM, 2 * SEQ, 32, 128, S64);
    make_map_nd(enc, &P.woA, A_wo, 3, {64, DM, 16}, {DM * 2, 128}, {64, 64, 4});
    make_map_nd(enc, &P.woB, B_wo, 5, {64, 32, 2, 16, 16}, {DM * 2, 32 * DM * 2, 64 * DM * 2, 128}, {64, 32, 1, 2, 4});
    P.pxB = B_x; P.pwB = B_wqkv; P.pxA = A_x; P.pwA = A_wqkv; P.pwoA = A_wo; P.pwoB = B_wo; P.wphi = A_wphi;
    make_map(enc, &P.out, d_out, 2 * DM, SEQ, 64, 64, S128);
    fused_kernel<<<128, 512, SMEM_BYTES, cudaStreamPerThread>>>(P);
}
```
